```python
import torch

def _softmax(x, axis=-1):
    return torch.softmax(x, dim=axis)
def _gelu(x):
    return torch.nn.functional.gelu(x, approximate="tanh")
def _silu(x):
    return torch.nn.functional.silu(x)
def _sigmoid(x):
    return torch.sigmoid(x)
def _layernorm(x, axis=-1, eps=1e-5):
    m = x.mean(dim=axis, keepdim=True)
    v = x.var(dim=axis, keepdim=True, unbiased=False)
    return (x - m) / torch.sqrt(v + eps)
def _scatter_add(tgt, idx, src, axis=0):
    return tgt.clone().index_add_(axis, idx, src)
def _segment_sum(src, seg, n):
    out = torch.zeros((n,) + src.shape[1:], dtype=src.dtype)
    return out.index_add_(0, seg, src)
def _pad(x, pw):
    flat = tuple(v for pair in reversed(pw) for v in pair)
    return torch.nn.functional.pad(x, flat)

kernel_name = 'gated_mix__sliding_local_dilated__dense_activation_gelu__prompt'

def setup_inputs():

    _w = (lambda a: (lambda t: t.to(torch.bfloat16) if t.is_floating_point() else t)(torch.as_tensor(a)))
    def _A_setup():
        B, S, D = 1, 2048, 576
        return {
            "x": _w((lambda *s: torch.randn(*s, dtype=torch.bfloat16) * 0.05)(B, S, D)),
            "wqkv": _w((lambda *s: torch.randn(*s, dtype=torch.bfloat16) * 0.8)(D, 3 * D)),
            "wo": _w((lambda *s: torch.randn(*s, dtype=torch.bfloat16) * 0.05)(D, D)),
        }
    _A_in = _A_setup()

    def _B_setup():
        B, S, D, F = 1, 2048, 576, 4608
        return {
            "x": _w((lambda *s: torch.randn(*s, dtype=torch.bfloat16) * 0.05)(B, S, D)),
            "w1": _w((lambda *s: torch.randn(*s, dtype=torch.bfloat16) * 12.8)(D, F) * (D ** -0.5)),
            "b1": _w((lambda *s: torch.randn(*s, dtype=torch.bfloat16) * 12.8)(F) * 0.01),
            "w2": _w((lambda *s: torch.randn(*s, dtype=torch.bfloat16) * 1.6)(F, D) * (F ** -0.5)),
            "b2": _w((lambda *s: torch.randn(*s, dtype=torch.bfloat16) * 12.8)(D) * 0.01),
        }
    _B_in = _B_setup()

    return {
        "A_x": _A_in["x"],
        "A_wqkv": _A_in["wqkv"],
        "A_wo": _A_in["wo"],
        "B_x": _B_in["x"],
        "B_w1": _B_in["w1"],
        "B_b1": _B_in["b1"],
        "B_w2": _B_in["w2"],
        "B_b2": _B_in["b2"],
        "gate_w": _w((lambda *s: torch.randn(*s, dtype=torch.bfloat16) * 0.05)(576) * 16.0),
    }

def reference(A_x, A_wqkv, A_wo, B_x, B_w1, B_b1, B_w2, B_b2, gate_w):
    def _A_ref(x, wqkv, wo):
        B, S, D = x.shape
        H = 32; Dh = D // H
        W, dil = 8, 2
        qkv = (lambda x, *d: x.permute(*d))((x @ wqkv).reshape(B, S, 3, H, Dh), 2, 0, 3, 1, 4)
        q, k, v = qkv[0], qkv[1], qkv[2]
        scale = Dh ** -0.5
        pos = torch.arange(S)
        off = torch.arange(W) * dil
        idx = pos[:, None] - off[None, :]
        mask = idx >= 0
        idx_c = torch.where(mask, idx, 0).reshape(-1)
        kg = k[:, :, idx_c, :].reshape(B, H, S, W, Dh)
        vg = v[:, :, idx_c, :].reshape(B, H, S, W, Dh)
        logits = torch.einsum("bhsd,bhswd->bhsw", q, kg) * scale
        logits = torch.where(mask[None, None, :, :], logits, -1e9)
        attn = _softmax(logits, axis=-1)
        o = torch.einsum("bhsw,bhswd->bhsd", attn, vg)
        return (lambda x, *d: x.permute(*d))(o, 0, 2, 1, 3).reshape(B, S, D) @ wo

    def _B_ref(x, w1, b1, w2, b2):
        h = torch.einsum("bsd,df->bsf", x, w1) + b1
        h = _gelu(h)
        return torch.einsum("bsf,fd->bsd", h, w2) + b2

    x = A_x
    g = _sigmoid((x * gate_w).sum(-1, keepdims=True))
    a = _A_ref(x, A_wqkv, A_wo)
    b = _B_ref(x, B_w1, B_b1, B_w2, B_b2)
    return g * a + (1 - g) * b
```

```cpp
#include <cuda_runtime.h>
#include <cuda.h>
#include <cuda_bf16.h>
#include <stdint.h>

namespace {

constexpr int SEQ = 2048, DM = 576, FF = 4608;
constexpr int NCTA = 128;
#define EXPV 0
#define XW(x) x
#define XW2(x) x
#define XN(n) n
#define NOQST 0
#define ALS 7
#define B4P 32
#define S0N 12
#define S0L 8
#define QSL 6
#define STAGGER 3
constexpr uint32_t X_OFF = 0;
constexpr uint32_t ST_OFF = 147456;
constexpr uint32_t ST_BYTES = 16384;
constexpr uint32_t BIAS_OFF = ST_OFF + 5 * ST_BYTES;
constexpr uint32_t BAR_OFF = BIAS_OFF + 2304;
constexpr uint32_t SMEM_TOTAL = 232448;
constexpr uint32_t SB_OFF = 0;
constexpr uint32_t DS_OFF = 32768;
constexpr uint32_t ST2_OFF = 65536;
constexpr uint32_t WO8_OFF = ST_OFF + 81920;

enum : uint32_t {
  B_XFULL0 = 0, B_FULL = 1, B_XFULL = 10, B_DFULL = 19, B_LFULL = 21, B_SFREE = 27, B_QREADY = 31,
  B_EMPTY = 32, B_PEERFREE = 42, B_XFREE = 43, B_QDONE = 44, B_PDONE = 46, B_BIAS = 48
};
constexpr uint32_t ZP_OFF = BAR_OFF + 512;
constexpr uint32_t B2_OFF = ZP_OFF;
constexpr uint32_t S16_OFF = BAR_OFF + 448;
constexpr uint32_t B28_OFF = BIAS_OFF + 2048;
constexpr int FS = 8;

__device__ uint4 g_qkv[216 * 2048];
__device__ uint4 g_o[NCTA * 9 * 128];
__device__ float4 g_part[NCTA * 4 * 2048];
__device__ float2 g_sg[SEQ];
__device__ unsigned g_qflag[NCTA * FS];
__device__ unsigned g_pflag[NCTA * 4 * FS];
__device__ unsigned g_done;
#define PACC_B()
#define PACC_E(i)
#define TS(i)
#define TSW(i)

template <int BOFF, int BHI = 0x40000040>
__device__ __forceinline__ void wgmma_rs_n64(float (&d)[32], uint32_t a0, uint32_t a1, uint32_t a2, uint32_t a3, uint32_t blo, int scale_d) {
  asm volatile("{\n.reg .pred p;\n.reg .b32 bl;\n.reg .b64 bd;\nsetp.ne.b32 p, %38, 0;\n"
    "add.u32 bl, %36, %37;\nmov.b64 bd, {bl, %39};\n"
    "wgmma.mma_async.sync.aligned.m64n64k16.f32.bf16.bf16 {%0, %1, %2, %3, %4, %5, %6, %7, %8, %9, %10, %11, %12, %13, %14, %15, %16, %17, %18, %19, %20, %21, %22, %23, %24, %25, %26, %27, %28, %29, %30, %31}, {%32, %33, %34, %35}, bd, p, 1, 1, 1;\n}\n"
    : "+f"(d[0]), "+f"(d[1]), "+f"(d[2]), "+f"(d[3]), "+f"(d[4]), "+f"(d[5]), "+f"(d[6]), "+f"(d[7]), "+f"(d[8]), "+f"(d[9]), "+f"(d[10]), "+f"(d[11]), "+f"(d[12]), "+f"(d[13]), "+f"(d[14]), "+f"(d[15]), "+f"(d[16]), "+f"(d[17]), "+f"(d[18]), "+f"(d[19]), "+f"(d[20]), "+f"(d[21]), "+f"(d[22]), "+f"(d[23]), "+f"(d[24]), "+f"(d[25]), "+f"(d[26]), "+f"(d[27]), "+f"(d[28]), "+f"(d[29]), "+f"(d[30]), "+f"(d[31])
    : "r"(a0), "r"(a1), "r"(a2), "r"(a3), "r"(blo), "n"(BOFF >> 4), "r"(scale_d), "n"(BHI));
}
template <int AOFF, int BOFF>
__device__ __forceinline__ void wgmma_ss_n64(float (&d)[32], uint32_t alo, uint32_t blo, int scale_d) {
  asm volatile("{\n.reg .pred p;\n.reg .b32 al, bl;\n.reg .b64 ad, bd;\nsetp.ne.b32 p, %36, 0;\n"
    "add.u32 al, %32, %34;\nmov.b64 ad, {al, 0x40000040};\nadd.u32 bl, %33, %35;\nmov.b64 bd, {bl, 0x40000040};\n"
    "wgmma.mma_async.sync.aligned.m64n64k16.f32.bf16.bf16 {%0, %1, %2, %3, %4, %5, %6, %7, %8, %9, %10, %11, %12, %13, %14, %15, %16, %17, %18, %19, %20, %21, %22, %23, %24, %25, %26, %27, %28, %29, %30, %31}, ad, bd, p, 1, 1, 0, 1;\n}\n"
    : "+f"(d[0]), "+f"(d[1]), "+f"(d[2]), "+f"(d[3]), "+f"(d[4]), "+f"(d[5]), "+f"(d[6]), "+f"(d[7]), "+f"(d[8]), "+f"(d[9]), "+f"(d[10]), "+f"(d[11]), "+f"(d[12]), "+f"(d[13]), "+f"(d[14]), "+f"(d[15]), "+f"(d[16]), "+f"(d[17]), "+f"(d[18]), "+f"(d[19]), "+f"(d[20]), "+f"(d[21]), "+f"(d[22]), "+f"(d[23]), "+f"(d[24]), "+f"(d[25]), "+f"(d[26]), "+f"(d[27]), "+f"(d[28]), "+f"(d[29]), "+f"(d[30]), "+f"(d[31])
    : "r"(alo), "r"(blo), "n"(AOFF >> 4), "n"(BOFF >> 4), "r"(scale_d));
}
template <int AOFF, int BOFF>
__device__ __forceinline__ void wgmma_ss_n88(float (&d)[44], uint32_t alo, uint32_t blo, int scale_d) {
  asm volatile("{\n.reg .pred p;\n.reg .b32 al, bl;\n.reg .b64 ad, bd;\nsetp.ne.b32 p, %48, 0;\n"
    "add.u32 al, %44, %46;\nmov.b64 ad, {al, 0x40000040};\nadd.u32 bl, %45, %47;\nmov.b64 bd, {bl, 0x40000040};\n"
    "wgmma.mma_async.sync.aligned.m64n88k16.f32.bf16.bf16 {%0, %1, %2, %3, %4, %5, %6, %7, %8, %9, %10, %11, %12, %13, %14, %15, %16, %17, %18, %19, %20, %21, %22, %23, %24, %25, %26, %27, %28, %29, %30, %31, %32, %33, %34, %35, %36, %37, %38, %39, %40, %41, %42, %43}, ad, bd, p, 1, 1, 0, 1;\n}\n"
    : "+f"(d[0]), "+f"(d[1]), "+f"(d[2]), "+f"(d[3]), "+f"(d[4]), "+f"(d[5]), "+f"(d[6]), "+f"(d[7]), "+f"(d[8]), "+f"(d[9]), "+f"(d[10]), "+f"(d[11]), "+f"(d[12]), "+f"(d[13]), "+f"(d[14]), "+f"(d[15]), "+f"(d[16]), "+f"(d[17]), "+f"(d[18]), "+f"(d[19]), "+f"(d[20]), "+f"(d[21]), "+f"(d[22]), "+f"(d[23]), "+f"(d[24]), "+f"(d[25]), "+f"(d[26]), "+f"(d[27]), "+f"(d[28]), "+f"(d[29]), "+f"(d[30]), "+f"(d[31]), "+f"(d[32]), "+f"(d[33]), "+f"(d[34]), "+f"(d[35]), "+f"(d[36]), "+f"(d[37]), "+f"(d[38]), "+f"(d[39]), "+f"(d[40]), "+f"(d[41]), "+f"(d[42]), "+f"(d[43])
    : "r"(alo), "r"(blo), "n"(AOFF >> 4), "n"(BOFF >> 4), "r"(scale_d));
}
template <int AOFF, int BOFF>
__device__ __forceinline__ void wgmma_ss_n128(float (&d)[64], uint32_t alo, uint32_t blo, int scale_d) {
  asm volatile("{\n.reg .pred p;\n.reg .b32 al, bl;\n.reg .b64 ad, bd;\nsetp.ne.b32 p, %68, 0;\n"
    "add.u32 al, %64, %66;\nmov.b64 ad, {al, 0x40000040};\nadd.u32 bl, %65, %67;\nmov.b64 bd, {bl, 0x40000040};\n"
    "wgmma.mma_async.sync.aligned.m64n128k16.f32.bf16.bf16 {%0, %1, %2, %3, %4, %5, %6, %7, %8, %9, %10, %11, %12, %13, %14, %15, %16, %17, %18, %19, %20, %21, %22, %23, %24, %25, %26, %27, %28, %29, %30, %31, %32, %33, %34, %35, %36, %37, %38, %39, %40, %41, %42, %43, %44, %45, %46, %47, %48, %49, %50, %51, %52, %53, %54, %55, %56, %57, %58, %59, %60, %61, %62, %63}, ad, bd, p, 1, 1, 0, 1;\n}\n"
    : "+f"(d[0]), "+f"(d[1]), "+f"(d[2]), "+f"(d[3]), "+f"(d[4]), "+f"(d[5]), "+f"(d[6]), "+f"(d[7]), "+f"(d[8]), "+f"(d[9]), "+f"(d[10]), "+f"(d[11]), "+f"(d[12]), "+f"(d[13]), "+f"(d[14]), "+f"(d[15]), "+f"(d[16]), "+f"(d[17]), "+f"(d[18]), "+f"(d[19]), "+f"(d[20]), "+f"(d[21]), "+f"(d[22]), "+f"(d[23]), "+f"(d[24]), "+f"(d[25]), "+f"(d[26]), "+f"(d[27]), "+f"(d[28]), "+f"(d[29]), "+f"(d[30]), "+f"(d[31]), "+f"(d[32]), "+f"(d[33]), "+f"(d[34]), "+f"(d[35]), "+f"(d[36]), "+f"(d[37]), "+f"(d[38]), "+f"(d[39]), "+f"(d[40]), "+f"(d[41]), "+f"(d[42]), "+f"(d[43]), "+f"(d[44]), "+f"(d[45]), "+f"(d[46]), "+f"(d[47]), "+f"(d[48]), "+f"(d[49]), "+f"(d[50]), "+f"(d[51]), "+f"(d[52]), "+f"(d[53]), "+f"(d[54]), "+f"(d[55]), "+f"(d[56]), "+f"(d[57]), "+f"(d[58]), "+f"(d[59]), "+f"(d[60]), "+f"(d[61]), "+f"(d[62]), "+f"(d[63])
    : "r"(alo), "r"(blo), "n"(AOFF >> 4), "n"(BOFF >> 4), "r"(scale_d));
}

__device__ __forceinline__ uint32_t smem_u32(const void* p) { return (uint32_t)__cvta_generic_to_shared(p); }
__device__ __forceinline__ uint32_t mkdesc(uint32_t addr, uint32_t lbo) { return ((addr & 0x3FFFF) >> 4) | ((lbo >> 4) << 16); }
template <int I> struct IC { static constexpr int v = I; };
template <int B, int E, class F> __device__ __forceinline__ void static_for(F&& f) {
  if constexpr (B < E) { f(IC<B>{}); static_for<B + 1, E>(f); }
}
__device__ __forceinline__ void mbar_init(uint32_t bar, uint32_t cnt) { asm volatile("mbarrier.init.shared::cta.b64 [%0], %1;" :: "r"(bar), "r"(cnt)); }
__device__ __forceinline__ void mbar_expect_tx(uint32_t bar, uint32_t bytes) { asm volatile("mbarrier.arrive.expect_tx.shared::cta.b64 _, [%0], %1;" :: "r"(bar), "r"(bytes) : "memory"); }
__device__ __forceinline__ void mbar_arrive(uint32_t bar) { asm volatile("mbarrier.arrive.shared::cta.b64 _, [%0];" :: "r"(bar) : "memory"); }
__device__ __forceinline__ void mbar_arrive_remote(uint32_t raddr) { asm volatile("mbarrier.arrive.shared::cluster.b64 _, [%0];" :: "r"(raddr) : "memory"); }
__device__ __forceinline__ uint32_t mapa(uint32_t addr, uint32_t cta) { uint32_t r; asm("mapa.shared::cluster.u32 %0, %1, %2;" : "=r"(r) : "r"(addr), "r"(cta)); return r; }
__device__ __forceinline__ void mbar_wait(uint32_t bar, uint32_t parity) {
  asm volatile("{\n.reg .pred p;\n.reg .u32 n;\n"
    "mbarrier.try_wait.parity.shared::cta.b64 p, [%0], %1;\n@p bra W_DONE;\nmov.u32 n, 0;\n"
    "W_LOOP:\nmbarrier.try_wait.parity.shared::cta.b64 p, [%0], %1;\n@p bra W_DONE;\n"
    "add.u32 n, n, 1;\nsetp.lt.u32 p, n, 4194304;\n@p bra W_LOOP;\ntrap;\nW_DONE:\n}" :: "r"(bar), "r"(parity) : "memory");
}
__device__ __forceinline__ void tma_load(uint32_t dst, const CUtensorMap* tm, uint32_t bar, int c0, int c1) {
  asm volatile("cp.async.bulk.tensor.2d.shared::cluster.global.mbarrier::complete_tx::bytes [%0], [%1, {%3, %4}], [%2];"
    :: "r"(dst), "l"((uint64_t)tm), "r"(bar), "r"(c0), "r"(c1) : "memory");
}
__device__ __forceinline__ void bulk_prefetch(const void* p, uint32_t bytes) { asm volatile("cp.async.bulk.prefetch.L2.global [%0], %1;" :: "l"(p), "r"(bytes) : "memory"); }
__device__ __forceinline__ void l2_prefetch(const void* p) { asm volatile("prefetch.global.L2 [%0];" :: "l"(p)); }
__device__ __forceinline__ void bulk_load(uint32_t dst, const void* src, uint32_t bytes, uint32_t bar) {
  asm volatile("cp.async.bulk.shared::cluster.global.mbarrier::complete_tx::bytes [%0], [%1], %2, [%3];" :: "r"(dst), "l"(src), "r"(bytes), "r"(bar) : "memory");
}
__device__ __forceinline__ void bulk_store(void* dst, uint32_t src, uint32_t bytes) {
  asm volatile("cp.async.bulk.global.shared::cta.bulk_group [%0], [%1], %2;" :: "l"(dst), "r"(src), "r"(bytes) : "memory");
}
__device__ __forceinline__ void bulk_copy_peer(uint32_t rdst, uint32_t src, uint32_t bytes, uint32_t rbar) {
  asm volatile("cp.async.bulk.shared::cluster.shared::cta.mbarrier::complete_tx::bytes [%0], [%1], %2, [%3];" :: "r"(rdst), "r"(src), "r"(bytes), "r"(rbar) : "memory");
}
__device__ __forceinline__ void sts128(uint32_t addr, float a, float b, float c, float d) {
  asm volatile("st.shared.v4.f32 [%0], {%1,%2,%3,%4};" :: "r"(addr), "f"(a), "f"(b), "f"(c), "f"(d) : "memory");
}
__device__ __forceinline__ void wg_fence() { asm volatile("wgmma.fence.sync.aligned;" ::: "memory"); }
__device__ __forceinline__ void wg_commit() { asm volatile("wgmma.commit_group.sync.aligned;" ::: "memory"); }
template <int N> __device__ __forceinline__ void wg_wait() { asm volatile("wgmma.wait_group.sync.aligned %0;" :: "n"(N) : "memory"); }
template <int N> __device__ __forceinline__ void reg_fence(float (&d)[N]) {
#pragma unroll
  for (int i = 0; i < N; i++) asm volatile("" : "+f"(d[i]) :: "memory");
}
__device__ __forceinline__ uint32_t pack_bf16(float lo, float hi) { uint32_t r; asm("cvt.rn.bf16x2.f32 %0, %1, %2;" : "=r"(r) : "f"(hi), "f"(lo)); return r; }
__device__ __forceinline__ uint32_t pack_bf16v(float lo, float hi) { uint32_t r; asm volatile("cvt.rn.bf16x2.f32 %0, %1, %2;" : "=r"(r) : "f"(hi), "f"(lo)); return r; }
__device__ __forceinline__ float gelu2(float v) {
  float u = v * fmaf(v * v, 0.0356774081363f, 0.7978845608029f);
  float t; asm("tanh.approx.f32 %0, %1;" : "=f"(t) : "f"(u));
  return fmaf(v, t, v);
}
__device__ __forceinline__ void lds64v(float& a, float& b, uint32_t addr) { asm volatile("ld.volatile.shared.v2.f32 {%0, %1}, [%2];" : "=f"(a), "=f"(b) : "r"(addr)); }
__device__ __forceinline__ void lds64p(float& a, float& b, uint32_t base, uint32_t off) {
  asm volatile("{\n.reg .pred p;\nsetp.ne.u32 p, %2, 0;\n@p ld.volatile.shared.v2.f32 {%0, %1}, [%3];\n}" : "+f"(a), "+f"(b) : "r"(base), "r"(base + off));
}
template <int B, int E> __device__ __forceinline__ void reg_fence_r(float (&d)[64]) {
#pragma unroll
  for (int i = B; i < E; i++) asm volatile("" : "+f"(d[i]) :: "memory");
}
__device__ __forceinline__ float4 lds128(uint32_t addr) { float4 v; asm volatile("ld.shared.v4.f32 {%0,%1,%2,%3}, [%4];" : "=f"(v.x), "=f"(v.y), "=f"(v.z), "=f"(v.w) : "r"(addr) : "memory"); return v; }
__device__ __forceinline__ unsigned ld_acquire(const unsigned* p) { unsigned v; asm volatile("ld.acquire.gpu.global.u32 %0, [%1];" : "=r"(v) : "l"(p) : "memory"); return v; }
__device__ __forceinline__ void flag_set(unsigned* p, unsigned v) { asm volatile("st.release.gpu.global.u32 [%0], %1;" :: "l"(p), "r"(v) : "memory"); }
__device__ __forceinline__ void flag_wait(const unsigned* p, unsigned tag) {
  uint32_t it = 0;
  while (ld_acquire(p) != tag) { __nanosleep(40); if (++it > (1u << 22)) __trap(); }
}
__device__ __forceinline__ uint32_t ldg32(const void* p) { uint32_t v; asm volatile("ld.global.u32 %0, [%1];" : "=r"(v) : "l"(p) : "memory"); return v; }
__device__ __forceinline__ void mma16816(float (&c)[4], uint32_t a0, uint32_t a1, uint32_t a2, uint32_t a3, uint32_t b0, uint32_t b1) {
  asm volatile("mma.sync.aligned.m16n8k16.row.col.f32.bf16.bf16.f32 {%0,%1,%2,%3}, {%4,%5,%6,%7}, {%8,%9}, {%0,%1,%2,%3};"
    : "+f"(c[0]), "+f"(c[1]), "+f"(c[2]), "+f"(c[3]) : "r"(a0), "r"(a1), "r"(a2), "r"(a3), "r"(b0), "r"(b1));
}
__device__ __forceinline__ void mma1688(float (&c)[4], uint32_t a0, uint32_t a1, uint32_t b0) {
  asm volatile("mma.sync.aligned.m16n8k8.row.col.f32.bf16.bf16.f32 {%0,%1,%2,%3}, {%4,%5}, {%6}, {%0,%1,%2,%3};"
    : "+f"(c[0]), "+f"(c[1]), "+f"(c[2]), "+f"(c[3]) : "r"(a0), "r"(a1), "r"(b0));
}
__device__ __forceinline__ uint32_t movmat(uint32_t a) { uint32_t d; asm volatile("movmatrix.sync.aligned.m8n8.trans.b16 %0, %1;" : "=r"(d) : "r"(a)); return d; }

__device__ __forceinline__ uint32_t fresh_tid() { uint32_t t; asm volatile("mov.u32 %0, %%tid.x;" : "=r"(t)); return t; }

__device__ __forceinline__ void add_partial(float (&acc)[32], uint32_t addr) {
#pragma unroll
  for (int h = 0; h < 2; h++) {
#pragma unroll
    for (int j = 4 * h; j < 4 * h + 4; j++) {
      const float4 v = lds128(addr + j * 2048);
      acc[4 * j] += v.x; acc[4 * j + 1] += v.y; acc[4 * j + 2] += v.z; acc[4 * j + 3] += v.w;
    }
    reg_fence(acc);
    __syncwarp();
  }
}

struct Params {
  const __nv_bfloat16 *x, *wqkv, *wo, *w1, *w2;
  const __nv_bfloat16* b1;
  const __nv_bfloat16* b2;
  const __nv_bfloat16* gate_w;
  __nv_bfloat16* out;
};

__device__ __forceinline__ int p2_block(int c, int t) {
  if (t == 0) return 8;
  int d = (t - 1) >> 1, second = (t - 1) & 1, r = c & 1;
  int j = ((c >> 1) - d) & 3;
  return 2 * j + (second ? r : 1 - r);
}

template <int U0, class Epi>
__device__ __forceinline__ void ffn1_block128(float (&cur)[64], uint32_t bars, uint32_t xdesc, uint32_t bdesc, bool elect, Epi epi) {
  static_for<0, 9>([&](auto KB) {
    constexpr int kb = KB.v, u = U0 + kb, st = u % 5;
    mbar_wait(bars + (B_FULL + st) * 8, (u / 5) & 1);
    wg_fence();
    wgmma_ss_n128<kb * 16384, st * ST_BYTES>(cur, xdesc, bdesc, 1);
    wgmma_ss_n128<kb * 16384 + 32, st * ST_BYTES + 2048>(cur, xdesc, bdesc, 1);
    wg_commit();
    wg_wait<1>();
    if (elect) mbar_arrive(bars + (B_EMPTY + (u + 4) % 5) * 8);
    epi(2 * kb - 1);
    wg_fence();
    wgmma_ss_n128<kb * 16384 + 64, st * ST_BYTES + 4096>(cur, xdesc, bdesc, 1);
    wgmma_ss_n128<kb * 16384 + 96, st * ST_BYTES + 6144>(cur, xdesc, bdesc, 1);
    wg_commit();
    epi(2 * kb);
  });
}

template <int kb>
__device__ __forceinline__ void p2_kblock(float (&acc)[32], const uint32_t (&hf)[144], uint32_t bdesc, int init) {
  static_for<0, 4>([&](auto KS) {
    constexpr int k = kb * 4 + KS.v;
    wgmma_rs_n64<k * 2048>(acc, hf[4 * k], hf[4 * k + 1], hf[4 * k + 2], hf[4 * k + 3], bdesc, k > 0 ? 1 : init);
  });
}
__device__ __forceinline__ void p2_oblock(float (&acc)[32], const uint32_t (&of)[18], uint32_t bdesc, uint32_t odesc) {
  static_for<0, 4>([&](auto KS) {
    constexpr int ks = KS.v;
    wgmma_rs_n64<(36 + ks) * 2048>(acc, of[4 * ks], of[4 * ks + 1], of[4 * ks + 2], of[4 * ks + 3], bdesc, 1);
  });
  wgmma_rs_n64<0, 0x40000000>(acc, of[16], of[17], 0u, 0u, odesc, 1);
}

__global__ void __cluster_dims__(2, 1, 1) __launch_bounds__(384, 1)
fused_kernel(const __grid_constant__ CUtensorMap tm_x, const __grid_constant__ CUtensorMap tm_qkv,
             const __grid_constant__ CUtensorMap tm_w1, const __grid_constant__ CUtensorMap tm_w2,
             const __grid_constant__ CUtensorMap tm_wo, const __grid_constant__ CUtensorMap tm_wo8,
             const __grid_constant__ CUtensorMap tm_out, const Params prm) {
  extern __shared__ __align__(1024) uint8_t smem[];
  const uint32_t sb = smem_u32(smem);
  const uint32_t bars = sb + BAR_OFF;
  const int cta = blockIdx.x, m = cta >> 3, c = cta & 7;
  const int warp = __shfl_sync(~0u, threadIdx.x >> 5, 0), wg = warp >> 2, lane = threadIdx.x & 31;
  const int g = lane >> 2, q = lane & 3;

  uint32_t bw0[16];
  if (wg < 2) {
#pragma unroll
    for (int j = 0; j < 16; j++) bw0[j] = ldg32(prm.b1 + c * 576 + j * 8 + 2 * q);
  }
  if (lane == 0) {
    const int grp = warp == 8 ? 0 : warp == 0 ? 8 : warp;
    const uint32_t cnt = grp < 8 ? 1 : grp < 11 ? 2 : 4;
#pragma unroll
    for (int i = 0; i < 4; i++) mbar_init(bars + grp * 32 + i * 8, cnt);
    if (warp == 1) mbar_init(bars + B_BIAS * 8, 3);
    asm volatile("fence.mbarrier_init.release.cluster;" ::: "memory");
  }
  if (warp == 8) {
    asm volatile("bar.arrive 1, 384;" ::: "memory");
    if (lane == 0) {
      mbar_expect_tx(bars + B_XFULL0 * 8, 16384);
      tma_load(sb + X_OFF, &tm_x, bars + B_XFULL0 * 8, 0, m * 128);
      mbar_expect_tx(bars + B_FULL * 8, 16384);
      tma_load(sb + ST_OFF, &tm_qkv, bars + B_FULL * 8, c * 192, 0);
      tma_load(sb + ST_OFF + 8192, &tm_qkv, bars + B_FULL * 8, c * 192 + 64, 0);
      mbar_expect_tx(bars + (B_FULL + 1) * 8, 16384);
      tma_load(sb + ST_OFF + ST_BYTES, &tm_qkv, bars + (B_FULL + 1) * 8, c * 192 + 128, 0);
      tma_load(sb + ST_OFF + ST_BYTES + 8192, &tm_qkv, bars + (B_FULL + 1) * 8, 1536 + c * 24, 0);
    }
    asm volatile("bar.sync 6, 384;" ::: "memory");
  } else {
    asm volatile("bar.arrive 6, 384;" ::: "memory");
    asm volatile("bar.sync 1, 384;" ::: "memory");
  }
  asm volatile("barrier.cluster.arrive.relaxed.aligned;" ::: "memory");

  if (wg == 2) {
    asm volatile("setmaxnreg.dec.sync.aligned.u32 40;");
    if (warp == 8) {
      if (lane == 0) {
        uint32_t st = 2, ph = 1;
        auto stage = [&](uint32_t bytes, const CUtensorMap* ta, int a0, int a1, const CUtensorMap* tb, int b0, int b1, bool two) {
          const uint32_t bar = bars + (B_FULL + st) * 8, dst = sb + ST_OFF + st * ST_BYTES;
          mbar_wait(bars + (B_EMPTY + st) * 8, ph);
          mbar_expect_tx(bar, bytes);
          tma_load(dst, ta, bar, a0, a1);
          if (two) tma_load(dst + 8192, tb, bar, b0, b1);
          if (++st == 5) { st = 0; ph ^= 1; }
        };
#pragma unroll 1
        for (int u = 2; u < 18; u++) {
          const int xk = u < 4 ? ((u & 1) ? 9 : 1) : u - 2;
          if (xk < 9) {
            mbar_expect_tx(bars + (B_XFULL + xk) * 8, 16384);
            tma_load(sb + X_OFF + xk * 16384, &tm_x, bars + (B_XFULL + xk) * 8, xk * 64, m * 128);
          }
          const int c0 = c * 192 + (u & 1) * 128;
          stage(16384, &tm_qkv, c0, (u >> 1) * 64, &tm_qkv, (u & 1) ? 1536 + c * 24 : c0 + 64, (u >> 1) * 64, true);
          if (u == 4) {
            asm volatile("prefetch.tensormap [%0];" :: "l"((uint64_t)&tm_w1) : "memory");
            asm volatile("prefetch.tensormap [%0];" :: "l"((uint64_t)&tm_w2) : "memory");
            asm volatile("prefetch.tensormap [%0];" :: "l"((uint64_t)&tm_wo) : "memory");
            asm volatile("prefetch.tensormap [%0];" :: "l"((uint64_t)&tm_wo8) : "memory");
            asm volatile("prefetch.tensormap [%0];" :: "l"((uint64_t)&tm_out) : "memory");
          }
        }
#pragma unroll 1
        for (int b = 0; b < 4; b++)
#pragma unroll 1
          for (int kb = 0; kb < 9; kb++) stage(16384, &tm_w1, c * 576 + b * 128, kb * 64, &tm_w1, c * 576 + b * 128 + 64, kb * 64, true);
#pragma unroll 1
        for (int s = 0; s < 6; s++) {
          const bool two = s >= 1 && s <= 3;
          const int r0 = (s < 5 ? max(2 * s - 1, 0) : 8) * 64;
          stage(two ? 16384 : 8192, &tm_w1, c * 576 + 512, r0, &tm_w1, c * 576 + 512, r0 + 64, two);
        }
#pragma unroll 1
        for (int t = 0; t < 9; t++) {
          const int col = p2_block(c, t) * 64;
          const uint32_t set = (t & 1) * 5, base = sb + ((t & 1) ? ST2_OFF : ST_OFF);
          if (t == 1) mbar_wait(bars + B_XFREE * 8, 0);
#pragma unroll 1
          for (int s = 0; s < 5; s++) {
            const uint32_t bar = bars + (B_FULL + set + s) * 8, dst = base + s * ST_BYTES;
            mbar_wait(bars + (B_EMPTY + set + s) * 8, ((t >> 1) & 1) ^ 1);
            mbar_expect_tx(bar, s < 4 ? 16384 : 17408);
            tma_load(dst, &tm_w2, bar, col, c * 576 + s * 128);
            if (s < 4) {
              tma_load(dst + 8192, &tm_w2, bar, col, c * 576 + s * 128 + 64);
            } else {
              tma_load(dst + 8192, &tm_wo, bar, col, c * 72);
              tma_load(sb + WO8_OFF + (t & 1) * 1024, &tm_wo8, bar, col, c * 72 + 64);
            }
          }
        }
      }
      __syncwarp();
      asm volatile("barrier.cluster.wait.acquire.aligned;" ::: "memory");
    } else {
      const int wa = warp - 9;
      const unsigned tag = (*(volatile unsigned*)&g_done >> 7) + 1;
      {
        uint32_t bw[3];
        uint4 gw[3];
#pragma unroll
        for (int i = 0; i < 3; i++) bw[i] = *(const uint32_t*)(prm.b1 + c * 576 + 2 * (wa * 32 + lane + 96 * i));
#pragma unroll
        for (int i = 0; i < 3; i++) gw[i] = *(const uint4*)(prm.gate_w + (wa + 3 * i) * 64 + (lane & 7) * 8);
#pragma unroll
        for (int i = 0; i < 3; i++)
          asm volatile("st.shared.v2.u32 [%0], {%1, %2};" :: "r"(sb + BIAS_OFF + (wa * 32 + lane + 96 * i) * 8), "r"(bw[i] << 16), "r"(bw[i] & 0xffff0000u) : "memory");
        __syncwarp();
        if (lane == 0) mbar_arrive(bars + B_BIAS * 8);
        float z[4] = {0.f, 0.f, 0.f, 0.f};
#pragma unroll
        for (int i = 0; i < 3; i++) {
          const uint32_t w4[4] = {gw[i].x, gw[i].y, gw[i].z, gw[i].w};
          mbar_wait(bars + (wa + i == 0 ? B_XFULL0 : B_XFULL + wa + 3 * i) * 8, 0);
#pragma unroll
          for (int rr = 0; rr < 4; rr++) {
            const int r = c * 16 + rr * 4 + (lane >> 3);
            const float4 xv = lds128(sb + X_OFF + (wa + 3 * i) * 16384 + r * 128 + (((lane ^ r) & 7) << 4));
            const uint32_t xa[4] = {__float_as_uint(xv.x), __float_as_uint(xv.y), __float_as_uint(xv.z), __float_as_uint(xv.w)};
#pragma unroll
            for (int e = 0; e < 4; e++)
              z[rr] = fmaf(__uint_as_float(xa[e] << 16), __uint_as_float(w4[e] << 16), fmaf(__uint_as_float(xa[e] & 0xffff0000u), __uint_as_float(w4[e] & 0xffff0000u), z[rr]));
          }
        }
#pragma unroll
        for (int rr = 0; rr < 4; rr++) {
#pragma unroll
          for (int o = 4; o; o >>= 1) z[rr] += __shfl_xor_sync(~0u, z[rr], o);
          if ((lane & 7) == 0) asm volatile("st.shared.f32 [%0], %1;" :: "r"(sb + ZP_OFF + (rr * 4 + (lane >> 3)) * 16 + wa * 4), "f"(z[rr]) : "memory");
        }
      }
      asm volatile("barrier.cluster.wait.acquire.aligned;" ::: "memory");
      asm volatile("bar.sync 2, 96;" ::: "memory");
      if (wa == 1 && lane < 16) {
        const float4 zp = lds128(sb + ZP_OFF + lane * 16);
        const float e = __expf(fminf(zp.x + zp.y + zp.z, 60.f));
        g_sg[m * 128 + c * 16 + lane] = make_float2(2.f * e, __fdividef(0.5f, 1.f + e));
      }
      __syncwarp();
      TSW(40 + wa);
      if (wa == 0) {
        if (lane == 0) {
          auto fetch = [&](int f) {
            const int src = m * 8 + ((c + (f == 2 ? 6 : 4)) & 7);
            flag_wait(&g_pflag[(src * 4 + f + 1) * FS], tag);
            asm volatile("fence.proxy.async.global;" ::: "memory");
            if (f == 1) mbar_wait(bars + (B_SFREE + 1) * 8, 0);
#pragma unroll 1
            for (int v = 0; v < 2; v++) {
              const uint32_t vb = bars + v * 8;
              if (f > 0) mbar_wait(vb + (B_EMPTY + 3 + 2 * f) * 8, 1); else mbar_wait(bars + B_SFREE * 8, 0);
              mbar_expect_tx(vb + (B_LFULL + 2 * f) * 8, 16384);
              bulk_load(sb + v * 16384 + (f == 0 ? SB_OFF : ST2_OFF + (f - 1) * 32768), g_part + (size_t)(src * 4 + f + 1) * 2048 + v * 1024, 16384, vb + (B_LFULL + 2 * f) * 8);
            }
          };
          XW2(mbar_wait(bars + B_SFREE * 8, 0));
          XW2(mbar_wait(bars + B_SFREE * 8, 1));
#pragma unroll 1
          for (int f = 0; f < XN(3); f++) {
            fetch(f);
          }
        }
      } else if (wa == 1) {
        if (lane == 0) {
          mbar_wait(bars + B_QDONE * 8, 0);
          mbar_wait(bars + (B_QDONE + 1) * 8, 0);
          TSW(44);
          flag_set(&g_qflag[cta * FS], tag);
          TSW(46);
#pragma unroll 1
          for (int e = 0; e < XN(4); e++) {
#pragma unroll 1
            for (int w = 0; w < 2; w++) {
              mbar_wait(bars + (B_PDONE + w) * 8, e & 1);
              bulk_store(g_part + (size_t)(cta * 4 + e) * 2048 + w * 1024, sb + w * 16384 + SB_OFF, 16384);
            }
            asm volatile("cp.async.bulk.commit_group;" ::: "memory");
            if (e == 3) mbar_arrive(bars + (B_SFREE + 1) * 8);
            asm volatile("cp.async.bulk.wait_group.read 0;" ::: "memory");
            mbar_arrive(bars + (e < 3 ? B_SFREE : B_SFREE + 2) * 8);
            asm volatile("cp.async.bulk.wait_group 0;" ::: "memory");
            asm volatile("fence.proxy.async.global;" ::: "memory");
            flag_set(&g_pflag[(cta * 4 + e) * FS], tag);
          }
        }
      } else {
        mbar_wait(bars + (B_QDONE + 1) * 8, 0);
        if (lane < 8 || (lane < 16 && m > 0)) flag_wait(&g_qflag[(m * 8 + (lane < 8 ? lane : lane - 16)) * FS], tag);
        __syncwarp();
        if (lane == 0) mbar_arrive(bars + B_QREADY * 8);
        TSW(43);
        {
          const uint32_t bw = *(const uint32_t*)(prm.b2 + p2_block(c, 8) * 64 + 2 * lane);
          const uint32_t bw8 = *(const uint32_t*)(prm.b2 + 512 + 2 * lane);
          const float s16 = g_sg[m * 128 + c * 16 + (lane & 15)].y;
          asm volatile("st.shared.v2.f32 [%0], {%1, %2};" :: "r"(sb + B2_OFF + lane * 8), "f"(2.f * __uint_as_float(bw << 16)), "f"(2.f * __uint_as_float(bw & 0xffff0000u)) : "memory");
          if (lane < 16) asm volatile("st.shared.f32 [%0], %1;" :: "r"(sb + S16_OFF + lane * 4), "f"(s16) : "memory");
          mbar_wait(bars + B_XFREE * 8, 0);
          asm volatile("st.shared.v2.f32 [%0], {%1, %2};" :: "r"(sb + B28_OFF + lane * 8), "f"(2.f * __uint_as_float(bw8 << 16)), "f"(2.f * __uint_as_float(bw8 & 0xffff0000u)) : "memory");
          __syncwarp();
          if (lane < 3) mbar_arrive(bars + B_BIAS * 8);
        }
        XW2(mbar_wait(bars + B_SFREE * 8, 0));
        XW2(if (lane < 8) flag_wait(&g_pflag[(m * 8 + lane) * 4 * FS], tag));
        __syncwarp();
        if (lane == 0) {
          asm volatile("fence.proxy.async.global;" ::: "memory");
          XW2(mbar_wait(bars + (B_SFREE + 2) * 8, 0));
          mbar_expect_tx(bars + (B_SFREE + 3) * 8, 32768);
#pragma unroll 1
          for (int i = 0; i < 8; i++) bulk_load(sb + SB_OFF + i * 4096, g_part + (size_t)(m * 8 + i) * 8192 + c * 256, 4096, bars + (B_SFREE + 3) * 8);
        }
      }
      TSW(49 + wa);
    }
  } else {
    asm volatile("setmaxnreg.inc.sync.aligned.u32 232;");
    const bool elect = (threadIdx.x & 127) == 0;
    const int lrow = wg * 64 + (warp & 3) * 16 + g;
    const uint32_t xdesc = mkdesc(sb + X_OFF + wg * 8192, 16);
    const uint32_t bdesc = mkdesc(sb + ST_OFF, 8192);
    const uint32_t bias_addr = sb + BIAS_OFF + q * 8;
    uint32_t hf[144];
    float accB[64];
    {
      float accA[64];
#pragma unroll
      for (int j = 0; j < 16; j++) {
        const uint32_t bw = bw0[j];
        asm volatile("shl.b32 %0, %4, 16;\nand.b32 %1, %4, 0xffff0000;\nshl.b32 %2, %4, 16;\nand.b32 %3, %4, 0xffff0000;"
          : "=f"(accA[4 * j]), "=f"(accA[4 * j + 1]), "=f"(accA[4 * j + 2]), "=f"(accA[4 * j + 3]) : "r"(bw));
      }
      {
        float accQ[44];
        int st = 0; uint32_t ph = 0;
#pragma unroll 1
        for (int kb = 0; kb < 9; kb++) {
          const uint32_t ad = xdesc + kb * 1024;
          mbar_wait(bars + (kb == 0 ? B_XFULL0 : B_XFULL + kb) * 8, 0);
          mbar_wait(bars + (B_FULL + st) * 8, ph);
          if (kb == 0) TS(0);
          wg_fence();
          static_for<0, 4>([&](auto KS) { wgmma_ss_n128<KS.v * 32, KS.v * 2048>(accB, ad, bdesc + st * 1024, KS.v > 0 ? 1 : kb > 0); });
          wg_commit();
          if (kb > 0) {
            wg_wait<1>();
            if (elect) mbar_arrive(bars + (B_EMPTY + (st == 0 ? 4 : st - 1)) * 8);
          }
          if (++st == 5) { st = 0; ph ^= 1; }
          mbar_wait(bars + (B_FULL + st) * 8, ph);
          wg_fence();
          static_for<0, 4>([&](auto KS) { wgmma_ss_n88<KS.v * 32, KS.v * 2048>(accQ, ad, bdesc + st * 1024, KS.v > 0 ? 1 : kb > 0); });
          wg_commit();
          wg_wait<1>();
          if (elect) mbar_arrive(bars + (B_EMPTY + (st == 0 ? 4 : st - 1)) * 8);
          if (++st == 5) { st = 0; ph ^= 1; }
        }
        TS(1);
        char* qp = (char*)g_qkv + (size_t)(24 * c) * 32768 + (g & 1) * 16384 + (m * 8 + warp) * 128 + (g >> 1) * 32 + q * 8;
        char* qp2 = qp + (size_t)(168 - 21 * c) * 32768;
        ffn1_block128<18>(accA, bars, xdesc, bdesc, elect, [&](int i) {
          if (i < 0) { reg_fence(accQ); reg_fence(accB); mbar_wait(bars + B_BIAS * 8, 0); return; }
          if (i < QSL) {
#pragma unroll
            for (int j = (27 * i + QSL - 1) / QSL; j < (27 * i + 27 + QSL - 1) / QSL; j++) {
              if (NOQST) { asm volatile("" :: "f"(j < 16 ? accB[4 * (j & 15)] : accQ[(4 * j - 64) & 31])); }
              else if (j < 16) *(uint2*)(qp + j * 32768) = make_uint2(pack_bf16(accB[4 * j], accB[4 * j + 1]), pack_bf16(accB[4 * j + 2], accB[4 * j + 3]));
              else *(uint2*)((j < 24 ? qp : qp2) + j * 32768) = make_uint2(pack_bf16(accQ[4 * j - 64], accQ[4 * j - 63]), pack_bf16(accQ[4 * j - 62], accQ[4 * j - 61]));
            }
          }
          if (i == QSL) {
            __syncwarp();
            if (lane == 0) mbar_arrive(bars + (B_QDONE + wg) * 8);
          }
          if (i >= 6) {
#pragma unroll
            for (int p = 3 * (i - 6); p < 3 * (i - 5) && p < 32; p++) lds64p(accB[2 * p], accB[2 * p + 1], bias_addr, 512 + (p >> 1) * 32);
          }
        });
      }
      TS(2);
      uint32_t qa[2][9], kf[3][9], vf[3][9];
      float gs0, gs1;
      const int par = warp & 1, pr = m * 64 + (warp >> 1) * 16;
      const int row0 = (warp >> 1) * 32 + 2 * g + par;
      const char* abase = (const char*)g_qkv + (size_t)(9 * c) * 32768 + q * 8;
      const char* ap = abase + par * 16384 + (g & 3) * 32 + (g >> 2) * 4 + pr * 16;
      const char* ap0 = pr > 0 ? ap - 128 : abase;
      ffn1_block128<27>(accB, bars, xdesc, bdesc, elect, [&](int i) {
        if (i < 0) { reg_fence(accA); return; }
        if (i < 16) {
#pragma unroll
          for (int p = 2 * i; p < 2 * i + 2; p++) hf[p] = pack_bf16v(gelu2(accA[2 * p]), gelu2(accA[2 * p + 1]));
        }
        if (i >= ALS && i < ALS + 9) {
          const int j = i - ALS;
          if (j == 0) {
            mbar_wait(bars + B_QREADY * 8, 0);
            gs0 = g_sg[m * 128 + row0].x; gs1 = g_sg[m * 128 + row0 + 16].x;
          }
          qa[0][j] = ldg32(ap + j * 32768); qa[1][j] = ldg32(ap + j * 32768 + 128);
          kf[0][j] = ldg32(ap0 + (72 + j) * 32768); kf[1][j] = ldg32(ap + (72 + j) * 32768); kf[2][j] = ldg32(ap + (72 + j) * 32768 + 128);
          vf[0][j] = ldg32(ap0 + (144 + j) * 32768); vf[1][j] = ldg32(ap + (144 + j) * 32768); vf[2][j] = ldg32(ap + (144 + j) * 32768 + 128);
        }
      });
      TS(3);
      {
        const bool up0 = 2 * q > g, up1 = 2 * q + 1 > g;
        const uint32_t mk = (up0 ? 0xffffu : 0u) | (up1 ? 0xffff0000u : 0u);
        float l[4][4];
        static_for<0, 4>([&](auto H) {
          constexpr int h = H.v;
          const bool lo = q >= h, hi = q <= h;
          float s[3][4];
#pragma unroll
          for (int kt = 0; kt < 3; kt++) {
            s[kt][0] = s[kt][1] = s[kt][2] = s[kt][3] = 0.f;
            mma16816(s[kt], lo ? qa[0][2 * h] : 0u, lo ? qa[1][2 * h] : 0u, qa[0][2 * h + 1], qa[1][2 * h + 1], kf[kt][2 * h], kf[kt][2 * h + 1]);
            mma1688(s[kt], hi ? qa[0][2 * h + 2] : 0u, hi ? qa[1][2 * h + 2] : 0u, kf[kt][2 * h + 2]);
          }
          const float sc = 0.23570226039551584f * 1.4426950408889634f;
          l[h][0] = (up0 ? s[0][0] : s[1][0]) * sc; l[h][1] = (up1 ? s[0][1] : s[1][1]) * sc;
          l[h][2] = (up0 ? s[1][2] : s[2][2]) * sc; l[h][3] = (up1 ? s[1][3] : s[2][3]) * sc;
          if (pr == 0) { if (up0) l[h][0] = -1e9f * 1.4426950408889634f; if (up1) l[h][1] = -1e9f * 1.4426950408889634f; }
        });
        TS(30);
#pragma unroll
        for (int kt = 0; kt < 3; kt++)
#pragma unroll
          for (int j = 0; j < 9; j++) vf[kt][j] = movmat(vf[kt][j]);
        float mx[4][2], dn[4][2];
        uint32_t pt[4], pb[4];
#pragma unroll
        for (int h = 0; h < 4; h++) { mx[h][0] = fmaxf(l[h][0], l[h][1]); mx[h][1] = fmaxf(l[h][2], l[h][3]); }
#pragma unroll
        for (int o = 1; o <= 2; o++)
#pragma unroll
          for (int h = 0; h < 4; h++) { mx[h][0] = fmaxf(mx[h][0], __shfl_xor_sync(~0u, mx[h][0], o)); mx[h][1] = fmaxf(mx[h][1], __shfl_xor_sync(~0u, mx[h][1], o)); }
#pragma unroll
        for (int h = 0; h < 4; h++) {
#pragma unroll
          for (int e = 0; e < 4; e++) asm("ex2.approx.ftz.f32 %0, %1;" : "=f"(l[h][e]) : "f"(l[h][e] - mx[h][e >> 1]));
          dn[h][0] = l[h][0] + l[h][1]; dn[h][1] = l[h][2] + l[h][3];
        }
#pragma unroll
        for (int o = 1; o <= 2; o++)
#pragma unroll
          for (int h = 0; h < 4; h++) { dn[h][0] += __shfl_xor_sync(~0u, dn[h][0], o); dn[h][1] += __shfl_xor_sync(~0u, dn[h][1], o); }
#pragma unroll
        for (int h = 0; h < 4; h++) {
          const float f0 = __fdividef(gs0, dn[h][0]), f1 = __fdividef(gs1, dn[h][1]);
          pt[h] = pack_bf16(l[h][0] * f0, l[h][1] * f0); pb[h] = pack_bf16(l[h][2] * f1, l[h][3] * f1);
        }
        uint32_t ow[2][9];
#pragma unroll
        for (int i = 0; i < 12; i++) {
          const int h = i / 3, cgp = 2 * h + i % 3;
          float o[4] = {0.f, 0.f, 0.f, 0.f};
          mma16816(o, pt[h] & mk, 0u, pt[h] & ~mk, pb[h] & mk, vf[0][cgp], vf[1][cgp]);
          mma1688(o, 0u, pb[h] & ~mk, vf[2][cgp]);
          const uint32_t w0 = pack_bf16(o[0], o[1]), w1 = pack_bf16(o[2], o[3]);
          if (i % 3 == 0 && h > 0) { if (q >= h) { ow[0][cgp] = w0; ow[1][cgp] = w1; } }
          else { ow[0][cgp] = w0; ow[1][cgp] = w1; }
        }
        TS(31);
        char* ob = (char*)g_o + (size_t)cta * 18432 + warp * 2304 + lane * 8;
#pragma unroll
        for (int j = 0; j < 9; j++) *(uint2*)(ob + j * 256) = make_uint2(ow[0][j], ow[1][j]);
      }
    }
    float accC[32];
    {
      float accA[64];
#pragma unroll
      for (int p = 0; p < 32; p++) lds64v(accA[2 * p], accA[2 * p + 1], bias_addr + 1024 + (p >> 1) * 32);
      asm volatile("bar.sync 3, 256;" ::: "memory");
      TS(16);
      ffn1_block128<36>(accA, bars, xdesc, bdesc, elect, [&](int i) {
        if (i < 0) { reg_fence(accB); return; }
        if (i < 13) {
#pragma unroll
          for (int p = (5 * i + 1) / 2; p < (5 * i + 6) / 2 && p < 32; p++) hf[32 + p] = pack_bf16v(gelu2(accB[2 * p]), gelu2(accB[2 * p + 1]));
        } else {
#pragma unroll
          for (int p = 8 * (i - 13); p < 8 * (i - 12); p++) lds64v(accB[2 * p], accB[2 * p + 1], bias_addr + 1536 + (p >> 1) * 32);
        }
      });
      TS(4);
      ffn1_block128<45>(accB, bars, xdesc, bdesc, elect, [&](int i) {
        if (i < 0) { reg_fence(accA); return; }
#pragma unroll
        for (int p = 2 * i; p < 2 * i + 2 && p < 32; p++) hf[95 - p] = pack_bf16v(gelu2(accA[62 - 2 * p]), gelu2(accA[63 - 2 * p]));
        if (i == 16) {
#pragma unroll
          for (int p = 0; p < 16; p++) lds64v(accC[2 * p], accC[2 * p + 1], bias_addr + 2048 + (p >> 1) * 32);
        }
      });
    }
    TS(5);
    static_for<0, 18>([&](auto HB) {
      constexpr int hb = HB.v, kb = hb >> 1, s = kb < 7 ? (kb + 1) / 2 : kb - 3, u = 54 + s, st = u % 5;
      constexpr bool lead = kb == 0 || kb >= 7 || (kb & 1), first = lead && !(hb & 1);
      if (first) mbar_wait(bars + (B_FULL + st) * 8, (u / 5) & 1);
      wg_fence();
      static_for<(hb & 1) * 2, (hb & 1) * 2 + 2>([&](auto KS) {
        wgmma_ss_n64<kb * 16384 + KS.v * 32, st * ST_BYTES + (lead ? 0 : 8192) + KS.v * 2048>(accC, xdesc, bdesc, 1);
      });
      wg_commit();
      if (first) {
        wg_wait<1>();
        if (elect) mbar_arrive(bars + (B_EMPTY + (u + 4) % 5) * 8);
      }
      if (hb == 0) reg_fence(accB);
#pragma unroll
      for (int p = (B4P * hb + 17) / 18; p < (B4P * hb + B4P + 17) / 18; p++) {
        const int e = (p + 24) & 31;
        hf[96 + e] = pack_bf16v(gelu2(accB[2 * e]), gelu2(accB[2 * e + 1]));
      }
    });
    TS(6);
    asm volatile("barrier.cluster.wait.acquire.aligned;" ::: "memory");
    const uint32_t peer = (c & 1) ^ 1;
    uint32_t of[18];
    float acc[32];
    {
      static_for<0, 18>([&](auto HB) {
        constexpr int hb = HB.v, s = hb >> 2;
        if (!(hb & 3)) mbar_wait(bars + (B_FULL + s) * 8, 0);
        wg_fence();
        static_for<2 * hb, 2 * hb + 2>([&](auto K) {
          constexpr int k = K.v;
          wgmma_rs_n64<k * 2048>(acc, hf[4 * k], hf[4 * k + 1], hf[4 * k + 2], hf[4 * k + 3], bdesc, k > 0);
        });
        if (hb == 17) p2_oblock(acc, of, bdesc, mkdesc(sb + WO8_OFF, 8192));
        wg_commit();
        if (!(hb & 3)) {
          wg_wait<1>();
          if (elect) mbar_arrive(bars + (B_EMPTY + (s + 4) % 5) * 8);
        }
        if (hb == 0) {
          reg_fence(accC);
          if (elect) { mbar_arrive(bars + B_XFREE * 8); mbar_arrive_remote(mapa(bars + B_PEERFREE * 8, peer)); }
        }
        if (hb < S0N) {
    #pragma unroll
          for (int p = B4P + ((48 - B4P) * hb + S0N - 1) / S0N; p < B4P + ((48 - B4P) * (hb + 1) + S0N - 1) / S0N; p++) {
            if (p < 32) hf[88 + p] = pack_bf16v(gelu2(accB[2 * ((p - 8) & 31)]), gelu2(accB[2 * ((p - 8) & 31) + 1]));
            else hf[96 + p] = pack_bf16v(gelu2(accC[2 * (p & 15)]), gelu2(accC[2 * (p & 15) + 1]));
          }
        }
        if (hb == S0L) {
          const uint32_t ft = fresh_tid();
          const char* op = (const char*)g_o + (size_t)cta * 18432 + ((warp & 6) + ((ft >> 2) & 1)) * 2304 + ((ft >> 3) & 3) * 32 + (ft & 3) * 8 + (warp & 1) * 4;
#pragma unroll
          for (int i = 0; i < 9; i++) { of[2 * i] = ldg32(op + i * 256); of[2 * i + 1] = ldg32(op + i * 256 + 128); }
        }
      });
      wg_wait<0>();
      reg_fence(acc);
      if (elect) mbar_arrive(bars + (B_EMPTY + 4) * 8);
    }
    const uint32_t rbase = sb + wg * 14336 + fresh_tid() * 16;
    mbar_wait(bars + B_XFREE * 8, 0);
#pragma unroll
    for (int j = 0; j < 8; j++) sts128(sb + SB_OFF + warp * 4096 + (rbase & 0x1f0) + j * 512, acc[4 * j], acc[4 * j + 1], acc[4 * j + 2], acc[4 * j + 3]);
    asm volatile("fence.proxy.async.shared::cta;" ::: "memory");
    __syncwarp();
    if (lane == 0) mbar_arrive(bars + (B_PDONE + wg) * 8);
    TS(7);
#pragma unroll 1
    for (int t = 1; t < 9; t++) {
      const uint32_t ph = (t >> 1) & 1, sbars = bars + (t & 1) * 40;
      const uint32_t sdesc = mkdesc(sb + ((t & 1) ? ST2_OFF : ST_OFF), 8192), odesc = mkdesc(sb + WO8_OFF + (t & 1) * 1024, 8192);
      if (wg == 1) asm volatile("bar.sync %0, 256;" :: "r"(4 + (t & 1)) : "memory");
      static_for<0, 5>([&](auto S) {
        constexpr int s = S.v;
        PACC_B();
        mbar_wait(sbars + (B_FULL + s) * 8, ph);
        PACC_E(0);
        wg_fence();
        p2_kblock<2 * s>(acc, hf, sdesc, 0);
        if constexpr (s < 4) p2_kblock<2 * s + 1>(acc, hf, sdesc, 1); else p2_oblock(acc, of, sdesc, odesc);
        wg_commit();
        if (s == STAGGER && wg == 0) asm volatile("bar.arrive %0, 256;" :: "r"(4 + (t & 1)) : "memory");
        if (s > 0) {
          wg_wait<1>();
          if (elect) mbar_arrive(sbars + (B_EMPTY + s - 1) * 8);
        }
      });
      wg_wait<0>();
      reg_fence(acc);
      PACC_B();
      if (elect) mbar_arrive(sbars + (B_EMPTY + 4) * 8);
      if (t & 1) {
        if (t == 1) mbar_wait(bars + B_PEERFREE * 8, 0);
        XW(mbar_wait(bars + (B_QDONE + wg) * 8, ph));
        const uint32_t rdst = mapa(rbase + DS_OFF, peer), rbar = mapa(bars + (B_DFULL + wg) * 8, peer);
#pragma unroll
        for (int j = 0; j < 8; j++)
          asm volatile("st.async.weak.shared::cluster.mbarrier::complete_tx::bytes.v4.f32 [%0], {%1,%2,%3,%4}, [%5];"
            :: "r"(rdst + j * 2048), "f"(acc[4 * j]), "f"(acc[4 * j + 1]), "f"(acc[4 * j + 2]), "f"(acc[4 * j + 3]), "r"(rbar) : "memory");
        if (elect) mbar_expect_tx(bars + (B_DFULL + wg) * 8, 16384);
      } else {
        XW(mbar_wait(bars + (B_DFULL + wg) * 8, ph ^ 1));
        add_partial(acc, rbase + DS_OFF);
        if (t < 8) {
          if (lane == 0) mbar_arrive_remote(mapa(bars + (B_QDONE + wg) * 8, peer));
          if (t == 6) {
            XW(mbar_wait(bars + (B_LFULL + wg) * 8, 0));
            add_partial(acc, rbase + SB_OFF);
          } else {
            XW(mbar_wait(bars + B_SFREE * 8, ph ^ 1));
          }
#pragma unroll
          for (int j = 0; j < 8; j++) sts128(rbase + SB_OFF + j * 2048, acc[4 * j], acc[4 * j + 1], acc[4 * j + 2], acc[4 * j + 3]);
          asm volatile("fence.proxy.async.shared::cta;" ::: "memory");
          __syncwarp();
          if (lane == 0) mbar_arrive(bars + (B_PDONE + wg) * 8);
        }
      }
      PACC_E(1);
      TS(7 + t);
    }
    {
      const uint32_t ft = fresh_tid();
      const uint32_t ost = sb + ST2_OFF + 65536 + (ft >> 5) * 2048 + ((ft >> 2) & 7) * 128 + (ft & 3) * 4;
      const float2* sp = g_sg + m * 128 + (ft >> 5) * 16 + ((ft >> 2) & 7);
      const float s0 = __uint_as_float(ldg32(&sp[0].y)), s1 = __uint_as_float(ldg32(&sp[8].y));
      mbar_wait(bars + B_BIAS * 8, 1);
      mbar_wait(bars + (B_SFREE + 3) * 8, 0);
      {
        float4 a = lds128(sb + SB_OFF + ft * 16);
#pragma unroll
        for (int i = 1; i < 8; i++) { const float4 v = lds128(sb + SB_OFF + i * 4096 + ft * 16); a.x += v.x; a.y += v.y; a.z += v.z; a.w += v.w; }
        float bx, by, t0, t1;
        lds64v(bx, by, sb + B28_OFF + (ft >> 5) * 32 + (ft & 3) * 8);
        asm volatile("ld.shared.f32 %0, [%1];" : "=f"(t0) : "r"(sb + S16_OFF + (ft & 28)));
        asm volatile("ld.shared.f32 %0, [%1];" : "=f"(t1) : "r"(sb + S16_OFF + 32 + (ft & 28)));
        __nv_bfloat16* o8 = prm.out + (size_t)(m * 128 + c * 16 + ((ft >> 2) & 7)) * DM + 512 + (ft >> 5) * 8 + 2 * (ft & 3);
        *(uint32_t*)o8 = pack_bf16((a.x + bx) * t0, (a.y + by) * t0);
        *(uint32_t*)(o8 + 8 * DM) = pack_bf16((a.z + bx) * t1, (a.w + by) * t1);
      }
      mbar_wait(bars + (B_EMPTY + 9) * 8, 1);
      XW2(mbar_wait(bars + (B_LFULL + 2 + wg) * 8, 0));
      XW2(mbar_wait(bars + (B_LFULL + 4 + wg) * 8, 0));
#pragma unroll
      for (int j = 0; j < 8; j++) {
        float4 v = lds128(rbase + ST2_OFF + 32768 + j * 2048);
        const float4 w = lds128(rbase + ST2_OFF + j * 2048);
        v.x += w.x; v.y += w.y; v.z += w.z; v.w += w.w;
        float bx, by;
        lds64v(bx, by, sb + B2_OFF + (ft & 3) * 8 + j * 32);
        const uint32_t a = ost + ((j ^ ((ft >> 2) & 7)) << 4);
        asm volatile("st.shared.u32 [%0], %1;" :: "r"(a), "r"(pack_bf16((acc[4 * j] + v.x + bx) * s0, (acc[4 * j + 1] + v.y + by) * s0)) : "memory");
        asm volatile("st.shared.u32 [%0], %1;" :: "r"(a + 1024), "r"(pack_bf16((acc[4 * j + 2] + v.z + bx) * s1, (acc[4 * j + 3] + v.w + by) * s1)) : "memory");
      }
      asm volatile("fence.proxy.async.shared::cta;" ::: "memory");
      __syncwarp();
      if (lane == 0) {
        asm volatile("cp.async.bulk.tensor.2d.global.shared::cta.bulk_group [%0, {%2, %3}], [%1];"
          :: "l"((uint64_t)&tm_out), "r"(sb + ST2_OFF + 65536 + warp * 2048), "r"(p2_block(c, 8) * 64), "r"(m * 128 + warp * 16) : "memory");
        asm volatile("cp.async.bulk.commit_group;" ::: "memory");
        asm volatile("cp.async.bulk.wait_group.read 0;" ::: "memory");
      }
    }
    TS(17);
    if (threadIdx.x == 0) atomicAdd(&g_done, 1u);
  }
}

typedef CUresult (*EncodeFn)(CUtensorMap*, CUtensorMapDataType, cuuint32_t, void*, const cuuint64_t*, const cuuint64_t*,
                             const cuuint32_t*, const cuuint32_t*, CUtensorMapInterleave, CUtensorMapSwizzle,
                             CUtensorMapL2promotion, CUtensorMapFloatOOBfill);

CUtensorMap make_map(EncodeFn enc, const void* ptr, uint64_t rows, uint64_t cols, uint32_t box_rows) {
  CUtensorMap tm;
  cuuint64_t gd[2] = {cols, rows}; cuuint64_t gs[1] = {cols * 2};
  cuuint32_t bd[2] = {64, box_rows}; cuuint32_t es[2] = {1, 1};
  enc(&tm, CU_TENSOR_MAP_DATA_TYPE_BFLOAT16, 2, const_cast<void*>(ptr), gd, gs, bd, es, CU_TENSOR_MAP_INTERLEAVE_NONE,
      CU_TENSOR_MAP_SWIZZLE_128B, CU_TENSOR_MAP_L2_PROMOTION_L2_256B, CU_TENSOR_MAP_FLOAT_OOB_FILL_NONE);
  return tm;
}

}

extern "C" void kernel_launch(void* const* d_in, const int* in_sizes, int n_in, void* d_out, int out_size) {
  static EncodeFn enc = nullptr;
  if (!enc) {
    void* fn = nullptr; cudaDriverEntryPointQueryResult qr;
    cudaGetDriverEntryPoint("cuTensorMapEncodeTiled", &fn, cudaEnableDefault, &qr);
    enc = (EncodeFn)fn;
    cudaFuncSetAttribute(fused_kernel, cudaFuncAttributeMaxDynamicSharedMemorySize, SMEM_TOTAL);
  }
  CUtensorMap tx = make_map(enc, d_in[0], SEQ, DM, 128);
  CUtensorMap tq = make_map(enc, d_in[1], DM, 3 * DM, 64);
  CUtensorMap to = make_map(enc, d_in[2], DM, DM, 64);
  CUtensorMap to8 = make_map(enc, d_in[2], DM, DM, 8);
  CUtensorMap t1 = make_map(enc, d_in[4], DM, FF, 64);
  CUtensorMap t2 = make_map(enc, d_in[6], FF, DM, 64);
  CUtensorMap tout = make_map(enc, d_out, SEQ, DM, 16);
  Params prm;
  prm.x = (const __nv_bfloat16*)d_in[0];
  prm.wqkv = (const __nv_bfloat16*)d_in[1];
  prm.wo = (const __nv_bfloat16*)d_in[2];
  prm.w1 = (const __nv_bfloat16*)d_in[4];
  prm.w2 = (const __nv_bfloat16*)d_in[6];
  prm.b1 = (const __nv_bfloat16*)d_in[5];
  prm.b2 = (const __nv_bfloat16*)d_in[7];
  prm.gate_w = (const __nv_bfloat16*)d_in[8];
  prm.out = (__nv_bfloat16*)d_out;
  fused_kernel<<<NCTA, 384, SMEM_TOTAL, cudaStreamPerThread>>>(tx, tq, t1, t2, to, to8, tout, prm);
}
```

```cpp
#include <cuda_runtime.h>
#include <cuda.h>
#include <cuda_bf16.h>
#include <stdint.h>

namespace {

constexpr int SEQ = 2048, DM = 576, FF = 4608;
constexpr int NCTA = 128;
constexpr int QSL = 9;
constexpr int ALS = 8;
constexpr int B4P = 32;
constexpr int S0N = 12;
constexpr int S0L = 8;
constexpr int STAGGER = 2;
constexpr uint32_t X_OFF = 0;
constexpr uint32_t ST_OFF = 147456;
constexpr uint32_t ST_BYTES = 16384;
constexpr uint32_t BIAS_OFF = ST_OFF + 5 * ST_BYTES;
constexpr uint32_t BAR_OFF = BIAS_OFF + 2304;
constexpr uint32_t SMEM_TOTAL = 232448;
constexpr uint32_t SB_OFF = 0;
constexpr uint32_t DS_OFF = 32768;
constexpr uint32_t ST2_OFF = 65536;
constexpr uint32_t WO8_OFF = ST_OFF + 81920;

enum : uint32_t {
  B_XFULL0 = 0, B_FULL = 1, B_XFULL = 10, B_DFULL = 19, B_LFULL = 21, B_SFREE = 27, B_QREADY = 31,
  B_EMPTY = 32, B_PEERFREE = 42, B_XFREE = 43, B_QDONE = 44, B_PDONE = 46, B_BIAS = 48
};
constexpr uint32_t ZP_OFF = BAR_OFF + 512;
constexpr uint32_t B2_OFF = ZP_OFF;
constexpr uint32_t SR_OFF = WO8_OFF + 1024;
constexpr uint32_t B28_OFF = BIAS_OFF + 2048;
constexpr int FS = 8;

__device__ uint4 g_qkv[216 * 2048];
__device__ uint4 g_o[NCTA * 9 * 128];
__device__ float4 g_part[NCTA * 4 * 2048];
__device__ float2 g_sg[SEQ];
__device__ unsigned g_qflag[NCTA * FS];
__device__ unsigned g_pflag[NCTA * 4 * FS];
__device__ unsigned g_done;
#define PACC_B()
#define PACC_E(i)
#define TS(i)
#define TSW(i)

template <int BOFF, int BHI = 0x40000040>
__device__ __forceinline__ void wgmma_rs_n64(float (&d)[32], uint32_t a0, uint32_t a1, uint32_t a2, uint32_t a3, uint32_t blo, int scale_d) {
  asm volatile("{\n.reg .pred p;\n.reg .b32 bl;\n.reg .b64 bd;\nsetp.ne.b32 p, %38, 0;\n"
    "add.u32 bl, %36, %37;\nmov.b64 bd, {bl, %39};\n"
    "wgmma.mma_async.sync.aligned.m64n64k16.f32.bf16.bf16 {%0, %1, %2, %3, %4, %5, %6, %7, %8, %9, %10, %11, %12, %13, %14, %15, %16, %17, %18, %19, %20, %21, %22, %23, %24, %25, %26, %27, %28, %29, %30, %31}, {%32, %33, %34, %35}, bd, p, 1, 1, 1;\n}\n"
    : "+f"(d[0]), "+f"(d[1]), "+f"(d[2]), "+f"(d[3]), "+f"(d[4]), "+f"(d[5]), "+f"(d[6]), "+f"(d[7]), "+f"(d[8]), "+f"(d[9]), "+f"(d[10]), "+f"(d[11]), "+f"(d[12]), "+f"(d[13]), "+f"(d[14]), "+f"(d[15]), "+f"(d[16]), "+f"(d[17]), "+f"(d[18]), "+f"(d[19]), "+f"(d[20]), "+f"(d[21]), "+f"(d[22]), "+f"(d[23]), "+f"(d[24]), "+f"(d[25]), "+f"(d[26]), "+f"(d[27]), "+f"(d[28]), "+f"(d[29]), "+f"(d[30]), "+f"(d[31])
    : "r"(a0), "r"(a1), "r"(a2), "r"(a3), "r"(blo), "n"(BOFF >> 4), "r"(scale_d), "n"(BHI));
}
template <int AOFF, int BOFF>
__device__ __forceinline__ void wgmma_ss_n64(float (&d)[32], uint32_t alo, uint32_t blo, int scale_d) {
  asm volatile("{\n.reg .pred p;\n.reg .b32 al, bl;\n.reg .b64 ad, bd;\nsetp.ne.b32 p, %36, 0;\n"
    "add.u32 al, %32, %34;\nmov.b64 ad, {al, 0x40000040};\nadd.u32 bl, %33, %35;\nmov.b64 bd, {bl, 0x40000040};\n"
    "wgmma.mma_async.sync.aligned.m64n64k16.f32.bf16.bf16 {%0, %1, %2, %3, %4, %5, %6, %7, %8, %9, %10, %11, %12, %13, %14, %15, %16, %17, %18, %19, %20, %21, %22, %23, %24, %25, %26, %27, %28, %29, %30, %31}, ad, bd, p, 1, 1, 0, 1;\n}\n"
    : "+f"(d[0]), "+f"(d[1]), "+f"(d[2]), "+f"(d[3]), "+f"(d[4]), "+f"(d[5]), "+f"(d[6]), "+f"(d[7]), "+f"(d[8]), "+f"(d[9]), "+f"(d[10]), "+f"(d[11]), "+f"(d[12]), "+f"(d[13]), "+f"(d[14]), "+f"(d[15]), "+f"(d[16]), "+f"(d[17]), "+f"(d[18]), "+f"(d[19]), "+f"(d[20]), "+f"(d[21]), "+f"(d[22]), "+f"(d[23]), "+f"(d[24]), "+f"(d[25]), "+f"(d[26]), "+f"(d[27]), "+f"(d[28]), "+f"(d[29]), "+f"(d[30]), "+f"(d[31])
    : "r"(alo), "r"(blo), "n"(AOFF >> 4), "n"(BOFF >> 4), "r"(scale_d));
}
template <int AOFF, int BOFF>
__device__ __forceinline__ void wgmma_ss_n88(float (&d)[44], uint32_t alo, uint32_t blo, int scale_d) {
  asm volatile("{\n.reg .pred p;\n.reg .b32 al, bl;\n.reg .b64 ad, bd;\nsetp.ne.b32 p, %48, 0;\n"
    "add.u32 al, %44, %46;\nmov.b64 ad, {al, 0x40000040};\nadd.u32 bl, %45, %47;\nmov.b64 bd, {bl, 0x40000040};\n"
    "wgmma.mma_async.sync.aligned.m64n88k16.f32.bf16.bf16 {%0, %1, %2, %3, %4, %5, %6, %7, %8, %9, %10, %11, %12, %13, %14, %15, %16, %17, %18, %19, %20, %21, %22, %23, %24, %25, %26, %27, %28, %29, %30, %31, %32, %33, %34, %35, %36, %37, %38, %39, %40, %41, %42, %43}, ad, bd, p, 1, 1, 0, 1;\n}\n"
    : "+f"(d[0]), "+f"(d[1]), "+f"(d[2]), "+f"(d[3]), "+f"(d[4]), "+f"(d[5]), "+f"(d[6]), "+f"(d[7]), "+f"(d[8]), "+f"(d[9]), "+f"(d[10]), "+f"(d[11]), "+f"(d[12]), "+f"(d[13]), "+f"(d[14]), "+f"(d[15]), "+f"(d[16]), "+f"(d[17]), "+f"(d[18]), "+f"(d[19]), "+f"(d[20]), "+f"(d[21]), "+f"(d[22]), "+f"(d[23]), "+f"(d[24]), "+f"(d[25]), "+f"(d[26]), "+f"(d[27]), "+f"(d[28]), "+f"(d[29]), "+f"(d[30]), "+f"(d[31]), "+f"(d[32]), "+f"(d[33]), "+f"(d[34]), "+f"(d[35]), "+f"(d[36]), "+f"(d[37]), "+f"(d[38]), "+f"(d[39]), "+f"(d[40]), "+f"(d[41]), "+f"(d[42]), "+f"(d[43])
    : "r"(alo), "r"(blo), "n"(AOFF >> 4), "n"(BOFF >> 4), "r"(scale_d));
}
template <int AOFF, int BOFF>
__device__ __forceinline__ void wgmma_ss_n128(float (&d)[64], uint32_t alo, uint32_t blo, int scale_d) {
  asm volatile("{\n.reg .pred p;\n.reg .b32 al, bl;\n.reg .b64 ad, bd;\nsetp.ne.b32 p, %68, 0;\n"
    "add.u32 al, %64, %66;\nmov.b64 ad, {al, 0x40000040};\nadd.u32 bl, %65, %67;\nmov.b64 bd, {bl, 0x40000040};\n"
    "wgmma.mma_async.sync.aligned.m64n128k16.f32.bf16.bf16 {%0, %1, %2, %3, %4, %5, %6, %7, %8, %9, %10, %11, %12, %13, %14, %15, %16, %17, %18, %19, %20, %21, %22, %23, %24, %25, %26, %27, %28, %29, %30, %31, %32, %33, %34, %35, %36, %37, %38, %39, %40, %41, %42, %43, %44, %45, %46, %47, %48, %49, %50, %51, %52, %53, %54, %55, %56, %57, %58, %59, %60, %61, %62, %63}, ad, bd, p, 1, 1, 0, 1;\n}\n"
    : "+f"(d[0]), "+f"(d[1]), "+f"(d[2]), "+f"(d[3]), "+f"(d[4]), "+f"(d[5]), "+f"(d[6]), "+f"(d[7]), "+f"(d[8]), "+f"(d[9]), "+f"(d[10]), "+f"(d[11]), "+f"(d[12]), "+f"(d[13]), "+f"(d[14]), "+f"(d[15]), "+f"(d[16]), "+f"(d[17]), "+f"(d[18]), "+f"(d[19]), "+f"(d[20]), "+f"(d[21]), "+f"(d[22]), "+f"(d[23]), "+f"(d[24]), "+f"(d[25]), "+f"(d[26]), "+f"(d[27]), "+f"(d[28]), "+f"(d[29]), "+f"(d[30]), "+f"(d[31]), "+f"(d[32]), "+f"(d[33]), "+f"(d[34]), "+f"(d[35]), "+f"(d[36]), "+f"(d[37]), "+f"(d[38]), "+f"(d[39]), "+f"(d[40]), "+f"(d[41]), "+f"(d[42]), "+f"(d[43]), "+f"(d[44]), "+f"(d[45]), "+f"(d[46]), "+f"(d[47]), "+f"(d[48]), "+f"(d[49]), "+f"(d[50]), "+f"(d[51]), "+f"(d[52]), "+f"(d[53]), "+f"(d[54]), "+f"(d[55]), "+f"(d[56]), "+f"(d[57]), "+f"(d[58]), "+f"(d[59]), "+f"(d[60]), "+f"(d[61]), "+f"(d[62]), "+f"(d[63])
    : "r"(alo), "r"(blo), "n"(AOFF >> 4), "n"(BOFF >> 4), "r"(scale_d));
}

__device__ __forceinline__ uint32_t smem_u32(const void* p) { return (uint32_t)__cvta_generic_to_shared(p); }
__device__ __forceinline__ uint32_t mkdesc(uint32_t addr, uint32_t lbo) { return ((addr & 0x3FFFF) >> 4) | ((lbo >> 4) << 16); }
template <int I> struct IC { static constexpr int v = I; };
template <int B, int E, class F> __device__ __forceinline__ void static_for(F&& f) {
  if constexpr (B < E) { f(IC<B>{}); static_for<B + 1, E>(f); }
}
__device__ __forceinline__ void mbar_init(uint32_t bar, uint32_t cnt) { asm volatile("mbarrier.init.shared::cta.b64 [%0], %1;" :: "r"(bar), "r"(cnt)); }
__device__ __forceinline__ void mbar_expect_tx(uint32_t bar, uint32_t bytes) { asm volatile("mbarrier.arrive.expect_tx.shared::cta.b64 _, [%0], %1;" :: "r"(bar), "r"(bytes) : "memory"); }
__device__ __forceinline__ void mbar_arrive(uint32_t bar) { asm volatile("mbarrier.arrive.shared::cta.b64 _, [%0];" :: "r"(bar) : "memory"); }
__device__ __forceinline__ void mbar_arrive_remote(uint32_t raddr) { asm volatile("mbarrier.arrive.shared::cluster.b64 _, [%0];" :: "r"(raddr) : "memory"); }
__device__ __forceinline__ uint32_t mapa(uint32_t addr, uint32_t cta) { uint32_t r; asm("mapa.shared::cluster.u32 %0, %1, %2;" : "=r"(r) : "r"(addr), "r"(cta)); return r; }
__device__ __forceinline__ void mbar_wait(uint32_t bar, uint32_t parity) {
  asm volatile("{\n.reg .pred p;\n.reg .u32 n;\n"
    "mbarrier.try_wait.parity.shared::cta.b64 p, [%0], %1;\n@p bra W_DONE;\nmov.u32 n, 0;\n"
    "W_LOOP:\nmbarrier.try_wait.parity.shared::cta.b64 p, [%0], %1;\n@p bra W_DONE;\n"
    "add.u32 n, n, 1;\nsetp.lt.u32 p, n, 4194304;\n@p bra W_LOOP;\ntrap;\nW_DONE:\n}" :: "r"(bar), "r"(parity) : "memory");
}
__device__ __forceinline__ void tma_load(uint32_t dst, const CUtensorMap* tm, uint32_t bar, int c0, int c1) {
  asm volatile("cp.async.bulk.tensor.2d.shared::cluster.global.mbarrier::complete_tx::bytes [%0], [%1, {%3, %4}], [%2];"
    :: "r"(dst), "l"((uint64_t)tm), "r"(bar), "r"(c0), "r"(c1) : "memory");
}
__device__ __forceinline__ void bulk_load(uint32_t dst, const void* src, uint32_t bytes, uint32_t bar) {
  asm volatile("cp.async.bulk.shared::cluster.global.mbarrier::complete_tx::bytes [%0], [%1], %2, [%3];" :: "r"(dst), "l"(src), "r"(bytes), "r"(bar) : "memory");
}
__device__ __forceinline__ void bulk_store(void* dst, uint32_t src, uint32_t bytes) {
  asm volatile("cp.async.bulk.global.shared::cta.bulk_group [%0], [%1], %2;" :: "l"(dst), "r"(src), "r"(bytes) : "memory");
}
__device__ __forceinline__ void sts128(uint32_t addr, float a, float b, float c, float d) {
  asm volatile("st.shared.v4.f32 [%0], {%1,%2,%3,%4};" :: "r"(addr), "f"(a), "f"(b), "f"(c), "f"(d) : "memory");
}
__device__ __forceinline__ void wg_fence() { asm volatile("wgmma.fence.sync.aligned;" ::: "memory"); }
__device__ __forceinline__ void wg_commit() { asm volatile("wgmma.commit_group.sync.aligned;" ::: "memory"); }
template <int N> __device__ __forceinline__ void wg_wait() { asm volatile("wgmma.wait_group.sync.aligned %0;" :: "n"(N) : "memory"); }
template <int N> __device__ __forceinline__ void reg_fence(float (&d)[N]) {
#pragma unroll
  for (int i = 0; i < N; i++) asm volatile("" : "+f"(d[i]) :: "memory");
}
__device__ __forceinline__ uint32_t pack_bf16(float lo, float hi) { uint32_t r; asm("cvt.rn.bf16x2.f32 %0, %1, %2;" : "=r"(r) : "f"(hi), "f"(lo)); return r; }
__device__ __forceinline__ uint32_t pack_bf16v(float lo, float hi) { uint32_t r; asm volatile("cvt.rn.bf16x2.f32 %0, %1, %2;" : "=r"(r) : "f"(hi), "f"(lo)); return r; }
__device__ __forceinline__ float gelu2(float v) {
  float u = v * fmaf(v * v, 0.0356774081363f, 0.7978845608029f);
  float t; asm("tanh.approx.f32 %0, %1;" : "=f"(t) : "f"(u));
  return fmaf(v, t, v);
}
__device__ __forceinline__ void lds64v(float& a, float& b, uint32_t addr) { asm volatile("ld.volatile.shared.v2.f32 {%0, %1}, [%2];" : "=f"(a), "=f"(b) : "r"(addr)); }
__device__ __forceinline__ void lds64p(float& a, float& b, uint32_t base, uint32_t off) {
  asm volatile("{\n.reg .pred p;\nsetp.ne.u32 p, %2, 0;\n@p ld.volatile.shared.v2.f32 {%0, %1}, [%3];\n}" : "+f"(a), "+f"(b) : "r"(base), "r"(base + off));
}
__device__ __forceinline__ float4 lds128(uint32_t addr) { float4 v; asm volatile("ld.shared.v4.f32 {%0,%1,%2,%3}, [%4];" : "=f"(v.x), "=f"(v.y), "=f"(v.z), "=f"(v.w) : "r"(addr) : "memory"); return v; }
__device__ __forceinline__ unsigned ld_acquire(const unsigned* p) { unsigned v; asm volatile("ld.acquire.gpu.global.u32 %0, [%1];" : "=r"(v) : "l"(p) : "memory"); return v; }
__device__ __forceinline__ void flag_set(unsigned* p, unsigned v) { asm volatile("st.release.gpu.global.u32 [%0], %1;" :: "l"(p), "r"(v) : "memory"); }
__device__ __forceinline__ void flag_wait(const unsigned* p, unsigned tag) {
  uint32_t it = 0;
  while (ld_acquire(p) != tag) { __nanosleep(40); if (++it > (1u << 22)) __trap(); }
}
__device__ __forceinline__ uint32_t ldg32(const void* p) { uint32_t v; asm volatile("ld.global.u32 %0, [%1];" : "=r"(v) : "l"(p) : "memory"); return v; }
__device__ __forceinline__ void mma16816(float (&c)[4], uint32_t a0, uint32_t a1, uint32_t a2, uint32_t a3, uint32_t b0, uint32_t b1) {
  asm volatile("mma.sync.aligned.m16n8k16.row.col.f32.bf16.bf16.f32 {%0,%1,%2,%3}, {%4,%5,%6,%7}, {%8,%9}, {%0,%1,%2,%3};"
    : "+f"(c[0]), "+f"(c[1]), "+f"(c[2]), "+f"(c[3]) : "r"(a0), "r"(a1), "r"(a2), "r"(a3), "r"(b0), "r"(b1));
}
__device__ __forceinline__ void mma1688(float (&c)[4], uint32_t a0, uint32_t a1, uint32_t b0) {
  asm volatile("mma.sync.aligned.m16n8k8.row.col.f32.bf16.bf16.f32 {%0,%1,%2,%3}, {%4,%5}, {%6}, {%0,%1,%2,%3};"
    : "+f"(c[0]), "+f"(c[1]), "+f"(c[2]), "+f"(c[3]) : "r"(a0), "r"(a1), "r"(b0));
}
__device__ __forceinline__ uint32_t movmat(uint32_t a) { uint32_t d; asm volatile("movmatrix.sync.aligned.m8n8.trans.b16 %0, %1;" : "=r"(d) : "r"(a)); return d; }

__device__ __forceinline__ uint32_t fresh_tid() { uint32_t t; asm volatile("mov.u32 %0, %%tid.x;" : "=r"(t)); return t; }

__device__ __forceinline__ void add_partial(float (&acc)[32], uint32_t addr) {
#pragma unroll
  for (int h = 0; h < 2; h++) {
#pragma unroll
    for (int j = 4 * h; j < 4 * h + 4; j++) {
      const float4 v = lds128(addr + j * 2048);
      acc[4 * j] += v.x; acc[4 * j + 1] += v.y; acc[4 * j + 2] += v.z; acc[4 * j + 3] += v.w;
    }
    reg_fence(acc);
    __syncwarp();
  }
}

struct Params {
  const __nv_bfloat16 *x, *wqkv, *wo, *w1, *w2;
  const __nv_bfloat16* b1;
  const __nv_bfloat16* b2;
  const __nv_bfloat16* gate_w;
  __nv_bfloat16* out;
};

__device__ __forceinline__ int p2_block(int c, int t) {
  if (t == 0) return 8;
  int d = (t - 1) >> 1, second = (t - 1) & 1, r = c & 1;
  int j = ((c >> 1) - d) & 3;
  return 2 * j + (second ? r : 1 - r);
}

template <int U0, bool ZERO = false, class Epi>
__device__ __forceinline__ void ffn1_block128(float (&cur)[64], uint32_t bars, uint32_t xdesc, uint32_t bdesc, bool elect, Epi epi) {
  static_for<0, 9>([&](auto KB) {
    constexpr int kb = KB.v, u = U0 + kb, st = u % 5;
    mbar_wait(bars + (B_FULL + st) * 8, (u / 5) & 1);
    wg_fence();
    wgmma_ss_n128<kb * 16384, st * ST_BYTES>(cur, xdesc, bdesc, (ZERO && kb == 0) ? 0 : 1);
    wgmma_ss_n128<kb * 16384 + 32, st * ST_BYTES + 2048>(cur, xdesc, bdesc, 1);
    wg_commit();
    wg_wait<1>();
    if (elect) mbar_arrive(bars + (B_EMPTY + (u + 4) % 5) * 8);
    epi(2 * kb - 1);
    wg_fence();
    wgmma_ss_n128<kb * 16384 + 64, st * ST_BYTES + 4096>(cur, xdesc, bdesc, 1);
    wgmma_ss_n128<kb * 16384 + 96, st * ST_BYTES + 6144>(cur, xdesc, bdesc, 1);
    wg_commit();
    epi(2 * kb);
  });
}

template <int kb>
__device__ __forceinline__ void p2_kblock(float (&acc)[32], const uint32_t (&hf)[144], uint32_t bdesc, int init) {
  static_for<0, 4>([&](auto KS) {
    constexpr int k = kb * 4 + KS.v;
    wgmma_rs_n64<k * 2048>(acc, hf[4 * k], hf[4 * k + 1], hf[4 * k + 2], hf[4 * k + 3], bdesc, k > 0 ? 1 : init);
  });
}
__device__ __forceinline__ void p2_oblock(float (&acc)[32], const uint32_t (&of)[18], uint32_t bdesc, uint32_t odesc) {
  static_for<0, 4>([&](auto KS) {
    constexpr int ks = KS.v;
    wgmma_rs_n64<(36 + ks) * 2048>(acc, of[4 * ks], of[4 * ks + 1], of[4 * ks + 2], of[4 * ks + 3], bdesc, 1);
  });
  wgmma_rs_n64<0, 0x40000000>(acc, of[16], of[17], 0u, 0u, odesc, 1);
}

__global__ void __cluster_dims__(2, 1, 1) __launch_bounds__(384, 1)
fused_kernel(const __grid_constant__ CUtensorMap tm_x, const __grid_constant__ CUtensorMap tm_qkv,
             const __grid_constant__ CUtensorMap tm_w1, const __grid_constant__ CUtensorMap tm_w2,
             const __grid_constant__ CUtensorMap tm_wo, const __grid_constant__ CUtensorMap tm_wo8,
             const __grid_constant__ CUtensorMap tm_out, const __grid_constant__ CUtensorMap tm_xh, const Params prm) {
  extern __shared__ __align__(1024) uint8_t smem[];
  const uint32_t sb = smem_u32(smem);
  const uint32_t bars = sb + BAR_OFF;
  const int cta = blockIdx.x, m = cta >> 3, c = cta & 7;
  const int warp = __shfl_sync(~0u, threadIdx.x >> 5, 0), wg = warp >> 2, lane = threadIdx.x & 31;
  const int g = lane >> 2, q = lane & 3;

  uint32_t bw0[16];
  if (wg < 2) {
#pragma unroll
    for (int j = 0; j < 16; j++) bw0[j] = ldg32(prm.b1 + c * 576 + j * 8 + 2 * q);
  }
  if (lane == 0) {
    const int grp = warp == 8 ? 0 : warp == 0 ? 8 : warp;
    const uint32_t cnt = grp < 8 ? 1 : grp < 11 ? 2 : 4;
#pragma unroll
    for (int i = 0; i < 4; i++) mbar_init(bars + grp * 32 + i * 8, cnt);
    if (warp == 1) mbar_init(bars + B_BIAS * 8, 3);
    if (warp == 9) asm volatile("prefetch.tensormap [%0];" :: "l"((uint64_t)&tm_xh) : "memory");
    asm volatile("fence.mbarrier_init.release.cluster;" ::: "memory");
  }
  if (warp == 8) {
    asm volatile("bar.arrive 1, 384;" ::: "memory");
    if (lane == 0) {
      mbar_expect_tx(bars + B_XFULL0 * 8, 16384);
      tma_load(sb + X_OFF, &tm_x, bars + B_XFULL0 * 8, 0, m * 128);
      mbar_expect_tx(bars + B_FULL * 8, 16384);
      tma_load(sb + ST_OFF, &tm_qkv, bars + B_FULL * 8, c * 192, 0);
      tma_load(sb + ST_OFF + 8192, &tm_qkv, bars + B_FULL * 8, c * 192 + 64, 0);
      mbar_expect_tx(bars + (B_FULL + 1) * 8, 16384);
      tma_load(sb + ST_OFF + ST_BYTES, &tm_qkv, bars + (B_FULL + 1) * 8, c * 192 + 128, 0);
      tma_load(sb + ST_OFF + ST_BYTES + 8192, &tm_qkv, bars + (B_FULL + 1) * 8, 1536 + c * 24, 0);
    }
    asm volatile("bar.sync 6, 384;" ::: "memory");
  } else {
    asm volatile("bar.arrive 6, 384;" ::: "memory");
    asm volatile("bar.sync 1, 384;" ::: "memory");
  }
  asm volatile("barrier.cluster.arrive.relaxed.aligned;" ::: "memory");

  if (wg == 2) {
    asm volatile("setmaxnreg.dec.sync.aligned.u32 40;");
    if (warp == 8) {
      asm volatile("barrier.cluster.wait.acquire.aligned;" ::: "memory");
      if (lane == 0) {
        uint32_t st = 2, ph = 1;
        auto stage = [&](uint32_t bytes, const CUtensorMap* ta, int a0, int a1, const CUtensorMap* tb, int b0, int b1, bool two) {
          const uint32_t bar = bars + (B_FULL + st) * 8, dst = sb + ST_OFF + st * ST_BYTES;
          mbar_wait(bars + (B_EMPTY + st) * 8, ph);
          mbar_expect_tx(bar, bytes);
          tma_load(dst, ta, bar, a0, a1);
          if (two) tma_load(dst + 8192, tb, bar, b0, b1);
          if (++st == 5) { st = 0; ph ^= 1; }
        };
#pragma unroll 1
        for (int u = 2; u < 18; u++) {
          const int xk = u < 4 ? ((u & 1) ? 9 : 1) : u - 2;
          if (xk < 9) {
            mbar_expect_tx(bars + (B_XFULL + xk) * 8, 16384);
            asm volatile("cp.async.bulk.tensor.2d.shared::cluster.global.mbarrier::complete_tx::bytes.multicast::cluster [%0], [%1, {%3, %4}], [%2], %5;"
              :: "r"(sb + X_OFF + xk * 16384 + (c & 1) * 8192), "l"((uint64_t)&tm_xh), "r"(bars + (B_XFULL + xk) * 8), "r"(xk * 64), "r"(m * 128 + (c & 1) * 64), "h"((uint16_t)3) : "memory");
          }
          const int c0 = c * 192 + (u & 1) * 128;
          stage(16384, &tm_qkv, c0, (u >> 1) * 64, &tm_qkv, (u & 1) ? 1536 + c * 24 : c0 + 64, (u >> 1) * 64, true);
          if (u == 4) {
            asm volatile("prefetch.tensormap [%0];" :: "l"((uint64_t)&tm_w1) : "memory");
            asm volatile("prefetch.tensormap [%0];" :: "l"((uint64_t)&tm_w2) : "memory");
            asm volatile("prefetch.tensormap [%0];" :: "l"((uint64_t)&tm_wo) : "memory");
            asm volatile("prefetch.tensormap [%0];" :: "l"((uint64_t)&tm_wo8) : "memory");
            asm volatile("prefetch.tensormap [%0];" :: "l"((uint64_t)&tm_out) : "memory");
          }
        }
#pragma unroll 1
        for (int b = 0; b < 4; b++)
#pragma unroll 1
          for (int kb = 0; kb < 9; kb++) stage(16384, &tm_w1, c * 576 + b * 128, kb * 64, &tm_w1, c * 576 + b * 128 + 64, kb * 64, true);
#pragma unroll 1
        for (int s = 0; s < 6; s++) {
          const bool two = s >= 1 && s <= 3;
          const int r0 = (s < 5 ? max(2 * s - 1, 0) : 8) * 64;
          stage(two ? 16384 : 8192, &tm_w1, c * 576 + 512, r0, &tm_w1, c * 576 + 512, r0 + 64, two);
        }
#pragma unroll 1
        for (int t = 0; t < 9; t++) {
          const int col = p2_block(c, t) * 64;
          const uint32_t set = (t & 1) * 5, base = sb + ((t & 1) ? ST2_OFF : ST_OFF);
          if (t == 1) mbar_wait(bars + B_XFREE * 8, 0);
#pragma unroll 1
          for (int s = 0; s < 5; s++) {
            const uint32_t bar = bars + (B_FULL + set + s) * 8, dst = base + s * ST_BYTES;
            mbar_wait(bars + (B_EMPTY + set + s) * 8, ((t >> 1) & 1) ^ 1);
            mbar_expect_tx(bar, s < 4 ? 16384 : 17408);
            tma_load(dst, &tm_w2, bar, col, c * 576 + s * 128);
            if (s < 4) {
              tma_load(dst + 8192, &tm_w2, bar, col, c * 576 + s * 128 + 64);
            } else {
              tma_load(dst + 8192, &tm_wo, bar, col, c * 72);
              tma_load(sb + WO8_OFF + (t & 1) * 1024, &tm_wo8, bar, col, c * 72 + 64);
            }
          }
        }
      }
    } else {
      const int wa = warp - 9;
      const unsigned tag = (*(volatile unsigned*)&g_done >> 7) + 1;
      {
        uint32_t bw[3];
        uint4 gw[3];
#pragma unroll
        for (int i = 0; i < 3; i++) bw[i] = *(const uint32_t*)(prm.b1 + c * 576 + 2 * (wa * 32 + lane + 96 * i));
#pragma unroll
        for (int i = 0; i < 3; i++) gw[i] = *(const uint4*)(prm.gate_w + (wa + 3 * i) * 64 + (lane & 7) * 8);
#pragma unroll
        for (int i = 0; i < 3; i++)
          asm volatile("st.shared.v2.u32 [%0], {%1, %2};" :: "r"(sb + BIAS_OFF + (wa * 32 + lane + 96 * i) * 8), "r"(bw[i] << 16), "r"(bw[i] & 0xffff0000u) : "memory");
        __syncwarp();
        if (lane == 0) mbar_arrive(bars + B_BIAS * 8);
        float z[4] = {0.f, 0.f, 0.f, 0.f};
#pragma unroll
        for (int i = 0; i < 3; i++) {
          const uint32_t w4[4] = {gw[i].x, gw[i].y, gw[i].z, gw[i].w};
          mbar_wait(bars + (wa + i == 0 ? B_XFULL0 : B_XFULL + wa + 3 * i) * 8, 0);
#pragma unroll
          for (int rr = 0; rr < 4; rr++) {
            const int r = c * 16 + rr * 4 + (lane >> 3);
            const float4 xv = lds128(sb + X_OFF + (wa + 3 * i) * 16384 + r * 128 + (((lane ^ r) & 7) << 4));
            const uint32_t xa[4] = {__float_as_uint(xv.x), __float_as_uint(xv.y), __float_as_uint(xv.z), __float_as_uint(xv.w)};
#pragma unroll
            for (int e = 0; e < 4; e++)
              z[rr] = fmaf(__uint_as_float(xa[e] << 16), __uint_as_float(w4[e] << 16), fmaf(__uint_as_float(xa[e] & 0xffff0000u), __uint_as_float(w4[e] & 0xffff0000u), z[rr]));
          }
        }
#pragma unroll
        for (int rr = 0; rr < 4; rr++) {
#pragma unroll
          for (int o = 4; o; o >>= 1) z[rr] += __shfl_xor_sync(~0u, z[rr], o);
          if ((lane & 7) == 0) asm volatile("st.shared.f32 [%0], %1;" :: "r"(sb + ZP_OFF + (rr * 4 + (lane >> 3)) * 16 + wa * 4), "f"(z[rr]) : "memory");
        }
      }
      asm volatile("barrier.cluster.wait.acquire.aligned;" ::: "memory");
      asm volatile("bar.sync 2, 96;" ::: "memory");
      if (wa == 1 && lane < 16) {
        const float4 zp = lds128(sb + ZP_OFF + lane * 16);
        const float e = __expf(fminf(zp.x + zp.y + zp.z, 60.f));
        g_sg[m * 128 + c * 16 + lane] = make_float2(2.f * e, __fdividef(0.5f, 1.f + e));
      }
      __syncwarp();
      TSW(40 + wa);
      if (wa == 0) {
        if (lane == 0) {
          auto fetch = [&](int f) {
            const int src = m * 8 + ((c + (f == 2 ? 6 : 4)) & 7);
            flag_wait(&g_pflag[(src * 4 + f + 1) * FS], tag);
            asm volatile("fence.proxy.async.global;" ::: "memory");
            if (f == 1) mbar_wait(bars + (B_SFREE + 1) * 8, 0);
#pragma unroll 1
            for (int v = 0; v < 2; v++) {
              const uint32_t vb = bars + v * 8;
              if (f > 0) mbar_wait(vb + (B_EMPTY + 3 + 2 * f) * 8, 1); else mbar_wait(bars + B_SFREE * 8, 0);
              mbar_expect_tx(vb + (B_LFULL + 2 * f) * 8, 16384);
              bulk_load(sb + v * 16384 + (f == 0 ? SB_OFF : ST2_OFF + (f - 1) * 32768), g_part + (size_t)(src * 4 + f + 1) * 2048 + v * 1024, 16384, vb + (B_LFULL + 2 * f) * 8);
            }
          };
          mbar_wait(bars + B_SFREE * 8, 0);
          mbar_wait(bars + B_SFREE * 8, 1);
#pragma unroll 1
          for (int f = 0; f < 3; f++) {
            fetch(f);
          }
        }
      } else if (wa == 1) {
        if (lane == 0) {
          mbar_wait(bars + B_QDONE * 8, 0);
          mbar_wait(bars + (B_QDONE + 1) * 8, 0);
          TSW(44);
          flag_set(&g_qflag[cta * FS], tag);
          TSW(46);
#pragma unroll 1
          for (int e = 0; e < 4; e++) {
#pragma unroll 1
            for (int w = 0; w < 2; w++) {
              mbar_wait(bars + (B_PDONE + w) * 8, e & 1);
              bulk_store(g_part + (size_t)(cta * 4 + e) * 2048 + w * 1024, sb + w * 16384 + SB_OFF, 16384);
            }
            asm volatile("cp.async.bulk.commit_group;" ::: "memory");
            if (e == 3) mbar_arrive(bars + (B_SFREE + 1) * 8);
            asm volatile("cp.async.bulk.wait_group.read 0;" ::: "memory");
            mbar_arrive(bars + (e < 3 ? B_SFREE : B_SFREE + 2) * 8);
            asm volatile("cp.async.bulk.wait_group 0;" ::: "memory");
            asm volatile("fence.proxy.async.global;" ::: "memory");
            asm volatile("st.relaxed.gpu.global.u32 [%0], %1;" :: "l"(&g_pflag[(cta * 4 + e) * FS]), "r"(tag) : "memory");
          }
        }
      } else {
        mbar_wait(bars + (B_QDONE + 1) * 8, 0);
        if (lane < 8 || (lane < 16 && m > 0)) flag_wait(&g_qflag[(m * 8 + (lane < 8 ? lane : lane - 16)) * FS], tag);
        __syncwarp();
        if (lane == 0) mbar_arrive(bars + B_QREADY * 8);
        TSW(43);
        {
          const uint32_t bw = *(const uint32_t*)(prm.b2 + p2_block(c, 8) * 64 + 2 * lane);
          const uint32_t bw8 = *(const uint32_t*)(prm.b2 + 512 + 2 * lane);
          asm volatile("st.shared.v2.f32 [%0], {%1, %2};" :: "r"(sb + B2_OFF + lane * 8), "f"(2.f * __uint_as_float(bw << 16)), "f"(2.f * __uint_as_float(bw & 0xffff0000u)) : "memory");
          mbar_wait(bars + B_XFREE * 8, 0);
          asm volatile("st.shared.v2.f32 [%0], {%1, %2};" :: "r"(sb + B28_OFF + lane * 8), "f"(2.f * __uint_as_float(bw8 << 16)), "f"(2.f * __uint_as_float(bw8 & 0xffff0000u)) : "memory");
        }
        float sr[4];
#pragma unroll
        for (int i = 0; i < 4; i++) sr[i] = g_sg[m * 128 + lane * 4 + i].y;
        mbar_wait(bars + B_SFREE * 8, 0);
        if (lane < 8) flag_wait(&g_pflag[(m * 8 + lane) * 4 * FS], tag);
        __syncwarp();
        if (lane == 0) {
          asm volatile("fence.proxy.async.global;" ::: "memory");
          mbar_wait(bars + (B_SFREE + 2) * 8, 0);
          mbar_expect_tx(bars + (B_SFREE + 3) * 8, 32768);
#pragma unroll 1
          for (int i = 0; i < 8; i++) bulk_load(sb + SB_OFF + i * 4096, g_part + (size_t)(m * 8 + i) * 8192 + c * 256, 4096, bars + (B_SFREE + 3) * 8);
        }
        __syncwarp();
        mbar_wait(bars + (B_EMPTY + 9) * 8, 1);
        sts128(sb + SR_OFF + lane * 16, sr[0], sr[1], sr[2], sr[3]);
        __syncwarp();
        if (lane < 3) mbar_arrive(bars + B_BIAS * 8);
      }
      TSW(49 + wa);
    }
  } else {
    asm volatile("setmaxnreg.inc.sync.aligned.u32 232;");
    const bool elect = (threadIdx.x & 127) == 0;
    const uint32_t xdesc = mkdesc(sb + X_OFF + wg * 8192, 16);
    const uint32_t bdesc = mkdesc(sb + ST_OFF, 8192);
    const uint32_t bias_addr = sb + BIAS_OFF + q * 8;
    uint32_t hf[144], ow[2][9];
    float accB[64];
    {
      float accA[64];
#pragma unroll
      for (int j = 0; j < 16; j++) {
        const uint32_t bw = bw0[j];
        asm volatile("shl.b32 %0, %4, 16;\nand.b32 %1, %4, 0xffff0000;\nshl.b32 %2, %4, 16;\nand.b32 %3, %4, 0xffff0000;"
          : "=f"(accA[4 * j]), "=f"(accA[4 * j + 1]), "=f"(accA[4 * j + 2]), "=f"(accA[4 * j + 3]) : "r"(bw));
      }
      {
        float accQ[44];
        int st = 0; uint32_t ph = 0;
#pragma unroll 1
        for (int kb = 0; kb < 9; kb++) {
          const uint32_t ad = xdesc + kb * 1024;
          mbar_wait(bars + (kb == 0 ? B_XFULL0 : B_XFULL + kb) * 8, 0);
          mbar_wait(bars + (B_FULL + st) * 8, ph);
          if (kb == 0) TS(0);
          wg_fence();
          static_for<0, 4>([&](auto KS) { wgmma_ss_n128<KS.v * 32, KS.v * 2048>(accB, ad, bdesc + st * 1024, KS.v > 0 ? 1 : kb > 0); });
          wg_commit();
          if (kb > 0) {
            wg_wait<1>();
            if (elect) mbar_arrive(bars + (B_EMPTY + (st == 0 ? 4 : st - 1)) * 8);
          }
          if (++st == 5) { st = 0; ph ^= 1; }
          mbar_wait(bars + (B_FULL + st) * 8, ph);
          wg_fence();
          static_for<0, 4>([&](auto KS) { wgmma_ss_n88<KS.v * 32, KS.v * 2048>(accQ, ad, bdesc + st * 1024, KS.v > 0 ? 1 : kb > 0); });
          wg_commit();
          wg_wait<1>();
          if (elect) mbar_arrive(bars + (B_EMPTY + (st == 0 ? 4 : st - 1)) * 8);
          if (++st == 5) { st = 0; ph ^= 1; }
        }
        TS(1);
        char* qp = (char*)g_qkv + (size_t)(24 * c) * 32768 + (g & 1) * 16384 + (m * 8 + warp) * 128 + (g >> 1) * 32 + q * 8;
        char* qp2 = qp + (size_t)(168 - 21 * c) * 32768;
        ffn1_block128<18>(accA, bars, xdesc, bdesc, elect, [&](int i) {
          if (i < 0) { reg_fence(accQ); reg_fence(accB); mbar_wait(bars + B_BIAS * 8, 0); return; }
          if (i < QSL) {
#pragma unroll
            for (int j = (27 * i + QSL - 1) / QSL; j < (27 * i + 27 + QSL - 1) / QSL; j++) {
              if (j < 16) *(uint2*)(qp + j * 32768) = make_uint2(pack_bf16(accB[4 * j], accB[4 * j + 1]), pack_bf16(accB[4 * j + 2], accB[4 * j + 3]));
              else *(uint2*)((j < 24 ? qp : qp2) + j * 32768) = make_uint2(pack_bf16(accQ[4 * j - 64], accQ[4 * j - 63]), pack_bf16(accQ[4 * j - 62], accQ[4 * j - 61]));
            }
          }
          if (i == QSL) {
            __syncwarp();
            if (lane == 0) mbar_arrive(bars + (B_QDONE + wg) * 8);
          }
          if (i >= 6) {
#pragma unroll
            for (int p = 3 * (i - 6); p < 3 * (i - 5) && p < 32; p++) lds64p(accB[2 * p], accB[2 * p + 1], bias_addr, 512 + (p >> 1) * 32);
          }
        });
      }
      TS(2);
      uint32_t qa[2][9], kf[3][9], vf[3][9];
      float gs0, gs1;
      const int par = warp & 1, pr = m * 64 + (warp >> 1) * 16;
      const int row0 = (warp >> 1) * 32 + 2 * g + par;
      const char* abase = (const char*)g_qkv + (size_t)(9 * c) * 32768 + q * 8;
      const char* ap = abase + par * 16384 + (g & 3) * 32 + (g >> 2) * 4 + pr * 16;
      const char* ap0 = pr > 0 ? ap - 128 : abase;
      ffn1_block128<27>(accB, bars, xdesc, bdesc, elect, [&](int i) {
        if (i < 0) { reg_fence(accA); return; }
        if (i < 16) {
#pragma unroll
          for (int p = 2 * i; p < 2 * i + 2; p++) hf[p] = pack_bf16v(gelu2(accA[2 * p]), gelu2(accA[2 * p + 1]));
        }
        if (i >= ALS && i < ALS + 9) {
          const int j = i - ALS;
          if (j == 0) {
            mbar_wait(bars + B_QREADY * 8, 0);
            gs0 = g_sg[m * 128 + row0].x; gs1 = g_sg[m * 128 + row0 + 16].x;
          }
          qa[0][j] = ldg32(ap + j * 32768); qa[1][j] = ldg32(ap + j * 32768 + 128);
          kf[0][j] = ldg32(ap0 + (72 + j) * 32768); kf[1][j] = ldg32(ap + (72 + j) * 32768); kf[2][j] = ldg32(ap + (72 + j) * 32768 + 128);
          vf[0][j] = ldg32(ap0 + (144 + j) * 32768); vf[1][j] = ldg32(ap + (144 + j) * 32768); vf[2][j] = ldg32(ap + (144 + j) * 32768 + 128);
        }
      });
      TS(3);
      {
        const bool up0 = 2 * q > g, up1 = 2 * q + 1 > g;
        const uint32_t mk = (up0 ? 0xffffu : 0u) | (up1 ? 0xffff0000u : 0u);
        float l[4][4];
        static_for<0, 4>([&](auto H) {
          constexpr int h = H.v;
          const bool lo = q >= h, hi = q <= h;
          float s[3][4];
#pragma unroll
          for (int kt = 0; kt < 3; kt++) {
            s[kt][0] = s[kt][1] = s[kt][2] = s[kt][3] = 0.f;
            mma16816(s[kt], lo ? qa[0][2 * h] : 0u, lo ? qa[1][2 * h] : 0u, qa[0][2 * h + 1], qa[1][2 * h + 1], kf[kt][2 * h], kf[kt][2 * h + 1]);
            mma1688(s[kt], hi ? qa[0][2 * h + 2] : 0u, hi ? qa[1][2 * h + 2] : 0u, kf[kt][2 * h + 2]);
          }
          const float sc = 0.23570226039551584f * 1.4426950408889634f;
          l[h][0] = (up0 ? s[0][0] : s[1][0]) * sc; l[h][1] = (up1 ? s[0][1] : s[1][1]) * sc;
          l[h][2] = (up0 ? s[1][2] : s[2][2]) * sc; l[h][3] = (up1 ? s[1][3] : s[2][3]) * sc;
          if (pr == 0) { if (up0) l[h][0] = -1e9f * 1.4426950408889634f; if (up1) l[h][1] = -1e9f * 1.4426950408889634f; }
        });
        TS(30);
#pragma unroll
        for (int kt = 0; kt < 3; kt++)
#pragma unroll
          for (int j = 0; j < 9; j++) vf[kt][j] = movmat(vf[kt][j]);
        float mx[4][2], dn[4][2];
        uint32_t pt[4], pb[4];
#pragma unroll
        for (int h = 0; h < 4; h++) { mx[h][0] = fmaxf(l[h][0], l[h][1]); mx[h][1] = fmaxf(l[h][2], l[h][3]); }
#pragma unroll
        for (int o = 1; o <= 2; o++)
#pragma unroll
          for (int h = 0; h < 4; h++) { mx[h][0] = fmaxf(mx[h][0], __shfl_xor_sync(~0u, mx[h][0], o)); mx[h][1] = fmaxf(mx[h][1], __shfl_xor_sync(~0u, mx[h][1], o)); }
#pragma unroll
        for (int h = 0; h < 4; h++) {
#pragma unroll
          for (int e = 0; e < 4; e++) asm("ex2.approx.ftz.f32 %0, %1;" : "=f"(l[h][e]) : "f"(l[h][e] - mx[h][e >> 1]));
          dn[h][0] = l[h][0] + l[h][1]; dn[h][1] = l[h][2] + l[h][3];
        }
#pragma unroll
        for (int o = 1; o <= 2; o++)
#pragma unroll
          for (int h = 0; h < 4; h++) { dn[h][0] += __shfl_xor_sync(~0u, dn[h][0], o); dn[h][1] += __shfl_xor_sync(~0u, dn[h][1], o); }
#pragma unroll
        for (int h = 0; h < 4; h++) {
          const float f0 = __fdividef(gs0, dn[h][0]), f1 = __fdividef(gs1, dn[h][1]);
          pt[h] = pack_bf16(l[h][0] * f0, l[h][1] * f0); pb[h] = pack_bf16(l[h][2] * f1, l[h][3] * f1);
        }
#pragma unroll
        for (int i = 0; i < 12; i++) {
          const int h = i / 3, cgp = 2 * h + i % 3;
          float o[4] = {0.f, 0.f, 0.f, 0.f};
          mma16816(o, pt[h] & mk, 0u, pt[h] & ~mk, pb[h] & mk, vf[0][cgp], vf[1][cgp]);
          mma1688(o, 0u, pb[h] & ~mk, vf[2][cgp]);
          const uint32_t w0 = pack_bf16(o[0], o[1]), w1 = pack_bf16(o[2], o[3]);
          if (i % 3 == 0 && h > 0) { if (q >= h) { ow[0][cgp] = w0; ow[1][cgp] = w1; } }
          else { ow[0][cgp] = w0; ow[1][cgp] = w1; }
        }
        TS(31);
      }
    }
    float accC[32];
    {
      float accA[64];
      asm volatile("bar.sync 3, 256;" ::: "memory");
      TS(16);
      ffn1_block128<36, true>(accA, bars, xdesc, bdesc, elect, [&](int i) {
        if (i < 0) {
          reg_fence(accB);
          char* ob = (char*)g_o + (size_t)cta * 18432 + warp * 2304 + lane * 8;
#pragma unroll
          for (int j = 0; j < 9; j++) *(uint2*)(ob + j * 256) = make_uint2(ow[0][j], ow[1][j]);
          return;
        }
        if (i < 11) {
#pragma unroll
          for (int p = 3 * i; p < 3 * i + 3 && p < 32; p++) hf[32 + p] = pack_bf16v(gelu2(accB[2 * p]), gelu2(accB[2 * p + 1]));
        } else {
#pragma unroll
          for (int p = 6 * (i - 11); p < 6 * (i - 10) && p < 32; p++) lds64v(accB[2 * p], accB[2 * p + 1], bias_addr + 1536 + (p >> 1) * 32);
        }
      });
      TS(4);
      float bn[4];
      ffn1_block128<45>(accB, bars, xdesc, bdesc, elect, [&](int i) {
        if (i < 0) reg_fence(accA);
        if (i >= 0 && i < 12) {
#pragma unroll
          for (int k = (4 * i + 2) / 3; k < (4 * i + 6) / 3; k++) {
            const float bx = bn[2 * (k & 1)], by = bn[2 * (k & 1) + 1];
            hf[95 - 2 * k] = pack_bf16v(gelu2(accA[62 - 4 * k] + bx), gelu2(accA[63 - 4 * k] + by));
            hf[94 - 2 * k] = pack_bf16v(gelu2(accA[60 - 4 * k] + bx), gelu2(accA[61 - 4 * k] + by));
          }
        }
        if (i < 11) {
#pragma unroll
          for (int k = (4 * i + 6) / 3; k < (4 * i + 10) / 3; k++) lds64v(bn[2 * (k & 1)], bn[2 * (k & 1) + 1], bias_addr + 1024 + (15 - k) * 32);
        }
        if (i >= 12 && i < 16) {
#pragma unroll
          for (int p = 4 * (i - 12); p < 4 * (i - 11); p++) lds64v(accC[2 * p], accC[2 * p + 1], bias_addr + 2048 + (p >> 1) * 32);
        }
      });
    }
    TS(5);
    static_for<0, 18>([&](auto HB) {
      constexpr int hb = HB.v, kb = hb >> 1, s = kb < 7 ? (kb + 1) / 2 : kb - 3, u = 54 + s, st = u % 5;
      constexpr bool lead = kb == 0 || kb >= 7 || (kb & 1), first = lead && !(hb & 1);
      if (first) mbar_wait(bars + (B_FULL + st) * 8, (u / 5) & 1);
      wg_fence();
      static_for<(hb & 1) * 2, (hb & 1) * 2 + 2>([&](auto KS) {
        wgmma_ss_n64<kb * 16384 + KS.v * 32, st * ST_BYTES + (lead ? 0 : 8192) + KS.v * 2048>(accC, xdesc, bdesc, 1);
      });
      wg_commit();
      if (first) {
        wg_wait<1>();
        if (elect) mbar_arrive(bars + (B_EMPTY + (u + 4) % 5) * 8);
      }
      if (hb == 0) reg_fence(accB);
#pragma unroll
      for (int p = (B4P * hb + 17) / 18; p < (B4P * hb + B4P + 17) / 18; p++) {
        const int e = (p + 24) & 31;
        hf[96 + e] = pack_bf16v(gelu2(accB[2 * e]), gelu2(accB[2 * e + 1]));
      }
    });
    TS(6);
    asm volatile("bar.sync %0, 128;" :: "r"(7 + wg) : "memory");
    asm volatile("barrier.cluster.wait.acquire.aligned;" ::: "memory");
    const uint32_t peer = (c & 1) ^ 1;
    uint32_t of[18];
    float acc[32];
    {
      static_for<0, 18>([&](auto HB) {
        constexpr int hb = HB.v, s = hb >> 2;
        if (!(hb & 3)) mbar_wait(bars + (B_FULL + s) * 8, 0);
        wg_fence();
        static_for<2 * hb, 2 * hb + 2>([&](auto K) {
          constexpr int k = K.v;
          wgmma_rs_n64<k * 2048>(acc, hf[4 * k], hf[4 * k + 1], hf[4 * k + 2], hf[4 * k + 3], bdesc, k > 0);
        });
        if (hb == 17) p2_oblock(acc, of, bdesc, mkdesc(sb + WO8_OFF, 8192));
        wg_commit();
        if (!(hb & 3)) {
          wg_wait<1>();
          if (elect) mbar_arrive(bars + (B_EMPTY + (s + 4) % 5) * 8);
        }
        if (hb == 0) {
          reg_fence(accC);
          if (elect) { mbar_arrive(bars + B_XFREE * 8); mbar_arrive_remote(mapa(bars + B_PEERFREE * 8, peer)); }
        }
        if (hb < S0N) {
    #pragma unroll
          for (int p = B4P + ((48 - B4P) * hb + S0N - 1) / S0N; p < B4P + ((48 - B4P) * (hb + 1) + S0N - 1) / S0N; p++) {
            if (p < 32) hf[88 + p] = pack_bf16v(gelu2(accB[2 * ((p - 8) & 31)]), gelu2(accB[2 * ((p - 8) & 31) + 1]));
            else hf[96 + p] = pack_bf16v(gelu2(accC[2 * (p & 15)]), gelu2(accC[2 * (p & 15) + 1]));
          }
        }
        if (hb == S0L) {
          const uint32_t ft = fresh_tid();
          const char* op = (const char*)g_o + (size_t)cta * 18432 + ((warp & 6) + ((ft >> 2) & 1)) * 2304 + ((ft >> 3) & 3) * 32 + (ft & 3) * 8 + (warp & 1) * 4;
#pragma unroll
          for (int i = 0; i < 9; i++) { of[2 * i] = ldg32(op + i * 256); of[2 * i + 1] = ldg32(op + i * 256 + 128); }
        }
      });
      wg_wait<0>();
      reg_fence(acc);
      if (elect) mbar_arrive(bars + (B_EMPTY + 4) * 8);
    }
    const uint32_t rbase = sb + wg * 14336 + fresh_tid() * 16;
    mbar_wait(bars + B_XFREE * 8, 0);
#pragma unroll
    for (int j = 0; j < 8; j++) sts128(sb + SB_OFF + warp * 4096 + (rbase & 0x1f0) + j * 512, acc[4 * j], acc[4 * j + 1], acc[4 * j + 2], acc[4 * j + 3]);
    asm volatile("fence.proxy.async.shared::cta;" ::: "memory");
    __syncwarp();
    if (lane == 0) mbar_arrive(bars + (B_PDONE + wg) * 8);
    TS(7);
    const uint32_t wbars = __shfl_sync(~0u, bars + wg * 8, 0);
#pragma unroll 1
    for (int t = 1; t < 9; t++) {
      const uint32_t ph = (t >> 1) & 1, sbars = bars + (t & 1) * 40;
      const uint32_t sdesc = mkdesc(sb + ((t & 1) ? ST2_OFF : ST_OFF), 8192), odesc = mkdesc(sb + WO8_OFF + (t & 1) * 1024, 8192);
      if (wg == 1) asm volatile("bar.sync %0, 256;" :: "r"(4 + (t & 1)) : "memory");
      static_for<0, 5>([&](auto S) {
        constexpr int s = S.v;
        PACC_B();
        mbar_wait(sbars + (B_FULL + s) * 8, ph);
        PACC_E(0);
        wg_fence();
        p2_kblock<2 * s>(acc, hf, sdesc, 0);
        if constexpr (s < 4) p2_kblock<2 * s + 1>(acc, hf, sdesc, 1); else p2_oblock(acc, of, sdesc, odesc);
        wg_commit();
        if (s == STAGGER && wg == 0) asm volatile("bar.arrive %0, 256;" :: "r"(4 + (t & 1)) : "memory");
        if (s > 0) {
          wg_wait<1>();
          if (elect) mbar_arrive(sbars + (B_EMPTY + s - 1) * 8);
        }
      });
      wg_wait<0>();
      reg_fence(acc);
      PACC_B();
      if (elect) mbar_arrive(sbars + (B_EMPTY + 4) * 8);
      if (t & 1) {
        if (t == 1) mbar_wait(bars + B_PEERFREE * 8, 0);
        mbar_wait(wbars + B_QDONE * 8, ph);
        const uint32_t rdst = mapa(rbase + DS_OFF, peer), rbar = mapa(wbars + B_DFULL * 8, peer);
#pragma unroll
        for (int j = 0; j < 8; j++)
          asm volatile("st.async.weak.shared::cluster.mbarrier::complete_tx::bytes.v4.f32 [%0], {%1,%2,%3,%4}, [%5];"
            :: "r"(rdst + j * 2048), "f"(acc[4 * j]), "f"(acc[4 * j + 1]), "f"(acc[4 * j + 2]), "f"(acc[4 * j + 3]), "r"(rbar) : "memory");
        if (elect) mbar_expect_tx(wbars + B_DFULL * 8, 16384);
      } else {
        mbar_wait(wbars + B_DFULL * 8, ph ^ 1);
        add_partial(acc, rbase + DS_OFF);
        if (t < 8) {
          if (lane == 0) mbar_arrive_remote(mapa(wbars + B_QDONE * 8, peer));
          if (t == 6) {
            mbar_wait(wbars + B_LFULL * 8, 0);
            add_partial(acc, rbase + SB_OFF);
          } else {
            mbar_wait(bars + B_SFREE * 8, ph ^ 1);
          }
#pragma unroll
          for (int j = 0; j < 8; j++) sts128(rbase + SB_OFF + j * 2048, acc[4 * j], acc[4 * j + 1], acc[4 * j + 2], acc[4 * j + 3]);
          asm volatile("fence.proxy.async.shared::cta;" ::: "memory");
          __syncwarp();
          if (lane == 0) mbar_arrive(wbars + B_PDONE * 8);
        }
      }
      PACC_E(1);
      TS(7 + t);
    }
    {
      const uint32_t ft = fresh_tid();
      const uint32_t ost = sb + ST2_OFF + 65536 + (ft >> 5) * 2048 + ((ft >> 2) & 7) * 128 + (ft & 3) * 4;
      mbar_wait(bars + B_BIAS * 8, 1);
      float s0, s1;
      asm volatile("ld.shared.f32 %0, [%1];" : "=f"(s0) : "r"(sb + SR_OFF + (ft >> 5) * 64 + (ft & 28)) : "memory");
      asm volatile("ld.shared.f32 %0, [%1];" : "=f"(s1) : "r"(sb + SR_OFF + (ft >> 5) * 64 + 32 + (ft & 28)) : "memory");
      mbar_wait(wbars + (B_LFULL + 2) * 8, 0);
      mbar_wait(wbars + (B_LFULL + 4) * 8, 0);
#pragma unroll
      for (int j = 0; j < 8; j++) {
        float4 v = lds128(rbase + ST2_OFF + 32768 + j * 2048);
        const float4 w = lds128(rbase + ST2_OFF + j * 2048);
        v.x += w.x; v.y += w.y; v.z += w.z; v.w += w.w;
        float bx, by;
        lds64v(bx, by, sb + B2_OFF + (ft & 3) * 8 + j * 32);
        const uint32_t a = ost + ((j ^ ((ft >> 2) & 7)) << 4);
        asm volatile("st.shared.u32 [%0], %1;" :: "r"(a), "r"(pack_bf16((acc[4 * j] + v.x + bx) * s0, (acc[4 * j + 1] + v.y + by) * s0)) : "memory");
        asm volatile("st.shared.u32 [%0], %1;" :: "r"(a + 1024), "r"(pack_bf16((acc[4 * j + 2] + v.z + bx) * s1, (acc[4 * j + 3] + v.w + by) * s1)) : "memory");
      }
      asm volatile("fence.proxy.async.shared::cta;" ::: "memory");
      __syncwarp();
      if (lane == 0) {
        asm volatile("cp.async.bulk.tensor.2d.global.shared::cta.bulk_group [%0, {%2, %3}], [%1];"
          :: "l"((uint64_t)&tm_out), "r"(sb + ST2_OFF + 65536 + warp * 2048), "r"(p2_block(c, 8) * 64), "r"(m * 128 + warp * 16) : "memory");
        asm volatile("cp.async.bulk.commit_group;" ::: "memory");
      }
      mbar_wait(bars + (B_SFREE + 3) * 8, 0);
      {
        float4 a = lds128(sb + SB_OFF + ft * 16);
#pragma unroll
        for (int i = 1; i < 8; i++) { const float4 v = lds128(sb + SB_OFF + i * 4096 + ft * 16); a.x += v.x; a.y += v.y; a.z += v.z; a.w += v.w; }
        float bx, by, t0, t1;
        lds64v(bx, by, sb + B28_OFF + (ft >> 5) * 32 + (ft & 3) * 8);
        asm volatile("ld.shared.f32 %0, [%1];" : "=f"(t0) : "r"(sb + SR_OFF + c * 64 + (ft & 28)));
        asm volatile("ld.shared.f32 %0, [%1];" : "=f"(t1) : "r"(sb + SR_OFF + c * 64 + 32 + (ft & 28)));
        __nv_bfloat16* o8 = prm.out + (size_t)(m * 128 + c * 16 + ((ft >> 2) & 7)) * DM + 512 + (ft >> 5) * 8 + 2 * (ft & 3);
        *(uint32_t*)o8 = pack_bf16((a.x + bx) * t0, (a.y + by) * t0);
        *(uint32_t*)(o8 + 8 * DM) = pack_bf16((a.z + bx) * t1, (a.w + by) * t1);
      }
      if (lane == 0) asm volatile("cp.async.bulk.wait_group.read 0;" ::: "memory");
    }
    TS(17);
    if (threadIdx.x == 0) atomicAdd(&g_done, 1u);
  }
}

typedef CUresult (*EncodeFn)(CUtensorMap*, CUtensorMapDataType, cuuint32_t, void*, const cuuint64_t*, const cuuint64_t*,
                             const cuuint32_t*, const cuuint32_t*, CUtensorMapInterleave, CUtensorMapSwizzle,
                             CUtensorMapL2promotion, CUtensorMapFloatOOBfill);

CUtensorMap make_map(EncodeFn enc, const void* ptr, uint64_t rows, uint64_t cols, uint32_t box_rows) {
  CUtensorMap tm;
  cuuint64_t gd[2] = {cols, rows}; cuuint64_t gs[1] = {cols * 2};
  cuuint32_t bd[2] = {64, box_rows}; cuuint32_t es[2] = {1, 1};
  enc(&tm, CU_TENSOR_MAP_DATA_TYPE_BFLOAT16, 2, const_cast<void*>(ptr), gd, gs, bd, es, CU_TENSOR_MAP_INTERLEAVE_NONE,
      CU_TENSOR_MAP_SWIZZLE_128B, CU_TENSOR_MAP_L2_PROMOTION_L2_256B, CU_TENSOR_MAP_FLOAT_OOB_FILL_NONE);
  return tm;
}

}

extern "C" void kernel_launch(void* const* d_in, const int* in_sizes, int n_in, void* d_out, int out_size) {
  static EncodeFn enc = nullptr;
  if (!enc) {
    void* fn = nullptr; cudaDriverEntryPointQueryResult qr;
    cudaGetDriverEntryPoint("cuTensorMapEncodeTiled", &fn, cudaEnableDefault, &qr);
    enc = (EncodeFn)fn;
    cudaFuncSetAttribute(fused_kernel, cudaFuncAttributeMaxDynamicSharedMemorySize, SMEM_TOTAL);
  }
  CUtensorMap tx = make_map(enc, d_in[0], SEQ, DM, 128);
  CUtensorMap tq = make_map(enc, d_in[1], DM, 3 * DM, 64);
  CUtensorMap to = make_map(enc, d_in[2], DM, DM, 64);
  CUtensorMap to8 = make_map(enc, d_in[2], DM, DM, 8);
  CUtensorMap t1 = make_map(enc, d_in[4], DM, FF, 64);
  CUtensorMap t2 = make_map(enc, d_in[6], FF, DM, 64);
  CUtensorMap tout = make_map(enc, d_out, SEQ, DM, 16);
  CUtensorMap txh = make_map(enc, d_in[0], SEQ, DM, 64);
  Params prm;
  prm.x = (const __nv_bfloat16*)d_in[0];
  prm.wqkv = (const __nv_bfloat16*)d_in[1];
  prm.wo = (const __nv_bfloat16*)d_in[2];
  prm.w1 = (const __nv_bfloat16*)d_in[4];
  prm.w2 = (const __nv_bfloat16*)d_in[6];
  prm.b1 = (const __nv_bfloat16*)d_in[5];
  prm.b2 = (const __nv_bfloat16*)d_in[7];
  prm.gate_w = (const __nv_bfloat16*)d_in[8];
  prm.out = (__nv_bfloat16*)d_out;
  fused_kernel<<<NCTA, 384, SMEM_TOTAL, cudaStreamPerThread>>>(tx, tq, t1, t2, to, to8, tout, txh, prm);
}
```

```cpp
#include <cuda_runtime.h>
#include <cuda.h>
#include <cuda_bf16.h>
#include <stdint.h>

namespace {

constexpr int SEQ = 2048, DM = 576, FF = 4608;
constexpr int NCTA = 128;
constexpr int QSL = 9;
constexpr int ALS = 8;
constexpr int B4P = 32;
constexpr int S0N = 12;
constexpr int S0L = 8;
constexpr int STAGGER = 2;
constexpr uint32_t X_OFF = 0;
constexpr uint32_t ST_OFF = 147456;
constexpr uint32_t ST_BYTES = 16384;
constexpr uint32_t BIAS_OFF = ST_OFF + 5 * ST_BYTES;
constexpr uint32_t BAR_OFF = BIAS_OFF + 2304;
constexpr uint32_t SMEM_TOTAL = 232448;
constexpr uint32_t SB_OFF = 0;
constexpr uint32_t DS_OFF = 32768;
constexpr uint32_t ST2_OFF = 65536;
constexpr uint32_t WO8_OFF = ST_OFF + 81920;

enum : uint32_t {
  B_XFULL0 = 0, B_FULL = 1, B_XFULL = 10, B_DFULL = 19, B_LFULL = 21, B_SFREE = 27, B_QREADY = 31,
  B_EMPTY = 32, B_PEERFREE = 42, B_XFREE = 43, B_QDONE = 44, B_PDONE = 46, B_BIAS = 48
};
constexpr uint32_t ZP_OFF = BAR_OFF + 512;
constexpr uint32_t B2_OFF = ZP_OFF;
constexpr uint32_t SR_OFF = WO8_OFF + 1024;
constexpr uint32_t B28_OFF = BIAS_OFF + 2048;
constexpr int FS = 8;

__device__ uint4 g_qkv[216 * 2048];
__device__ uint4 g_o[NCTA * 9 * 128];
__device__ float4 g_part[NCTA * 4 * 2048];
__device__ float2 g_sg[SEQ];
__device__ unsigned g_qflag[NCTA * FS];
__device__ unsigned g_pflag[NCTA * 4 * FS];
__device__ unsigned g_done;
#define PACC_B()
#define PACC_E(i)
#define TS(i)
#define TSW(i)

template <int BOFF, int BHI = 0x40000040>
__device__ __forceinline__ void wgmma_rs_n64(float (&d)[32], uint32_t a0, uint32_t a1, uint32_t a2, uint32_t a3, uint32_t blo, int scale_d) {
  asm volatile("{\n.reg .pred p;\n.reg .b32 bl;\n.reg .b64 bd;\nsetp.ne.b32 p, %38, 0;\n"
    "add.u32 bl, %36, %37;\nmov.b64 bd, {bl, %39};\n"
    "wgmma.mma_async.sync.aligned.m64n64k16.f32.bf16.bf16 {%0, %1, %2, %3, %4, %5, %6, %7, %8, %9, %10, %11, %12, %13, %14, %15, %16, %17, %18, %19, %20, %21, %22, %23, %24, %25, %26, %27, %28, %29, %30, %31}, {%32, %33, %34, %35}, bd, p, 1, 1, 1;\n}\n"
    : "+f"(d[0]), "+f"(d[1]), "+f"(d[2]), "+f"(d[3]), "+f"(d[4]), "+f"(d[5]), "+f"(d[6]), "+f"(d[7]), "+f"(d[8]), "+f"(d[9]), "+f"(d[10]), "+f"(d[11]), "+f"(d[12]), "+f"(d[13]), "+f"(d[14]), "+f"(d[15]), "+f"(d[16]), "+f"(d[17]), "+f"(d[18]), "+f"(d[19]), "+f"(d[20]), "+f"(d[21]), "+f"(d[22]), "+f"(d[23]), "+f"(d[24]), "+f"(d[25]), "+f"(d[26]), "+f"(d[27]), "+f"(d[28]), "+f"(d[29]), "+f"(d[30]), "+f"(d[31])
    : "r"(a0), "r"(a1), "r"(a2), "r"(a3), "r"(blo), "n"(BOFF >> 4), "r"(scale_d), "n"(BHI));
}
template <int AOFF, int BOFF>
__device__ __forceinline__ void wgmma_ss_n64(float (&d)[32], uint32_t alo, uint32_t blo, int scale_d) {
  asm volatile("{\n.reg .pred p;\n.reg .b32 al, bl;\n.reg .b64 ad, bd;\nsetp.ne.b32 p, %36, 0;\n"
    "add.u32 al, %32, %34;\nmov.b64 ad, {al, 0x40000040};\nadd.u32 bl, %33, %35;\nmov.b64 bd, {bl, 0x40000040};\n"
    "wgmma.mma_async.sync.aligned.m64n64k16.f32.bf16.bf16 {%0, %1, %2, %3, %4, %5, %6, %7, %8, %9, %10, %11, %12, %13, %14, %15, %16, %17, %18, %19, %20, %21, %22, %23, %24, %25, %26, %27, %28, %29, %30, %31}, ad, bd, p, 1, 1, 0, 1;\n}\n"
    : "+f"(d[0]), "+f"(d[1]), "+f"(d[2]), "+f"(d[3]), "+f"(d[4]), "+f"(d[5]), "+f"(d[6]), "+f"(d[7]), "+f"(d[8]), "+f"(d[9]), "+f"(d[10]), "+f"(d[11]), "+f"(d[12]), "+f"(d[13]), "+f"(d[14]), "+f"(d[15]), "+f"(d[16]), "+f"(d[17]), "+f"(d[18]), "+f"(d[19]), "+f"(d[20]), "+f"(d[21]), "+f"(d[22]), "+f"(d[23]), "+f"(d[24]), "+f"(d[25]), "+f"(d[26]), "+f"(d[27]), "+f"(d[28]), "+f"(d[29]), "+f"(d[30]), "+f"(d[31])
    : "r"(alo), "r"(blo), "n"(AOFF >> 4), "n"(BOFF >> 4), "r"(scale_d));
}
template <int AOFF, int BOFF>
__device__ __forceinline__ void wgmma_ss_n88(float (&d)[44], uint32_t alo, uint32_t blo, int scale_d) {
  asm volatile("{\n.reg .pred p;\n.reg .b32 al, bl;\n.reg .b64 ad, bd;\nsetp.ne.b32 p, %48, 0;\n"
    "add.u32 al, %44, %46;\nmov.b64 ad, {al, 0x40000040};\nadd.u32 bl, %45, %47;\nmov.b64 bd, {bl, 0x40000040};\n"
    "wgmma.mma_async.sync.aligned.m64n88k16.f32.bf16.bf16 {%0, %1, %2, %3, %4, %5, %6, %7, %8, %9, %10, %11, %12, %13, %14, %15, %16, %17, %18, %19, %20, %21, %22, %23, %24, %25, %26, %27, %28, %29, %30, %31, %32, %33, %34, %35, %36, %37, %38, %39, %40, %41, %42, %43}, ad, bd, p, 1, 1, 0, 1;\n}\n"
    : "+f"(d[0]), "+f"(d[1]), "+f"(d[2]), "+f"(d[3]), "+f"(d[4]), "+f"(d[5]), "+f"(d[6]), "+f"(d[7]), "+f"(d[8]), "+f"(d[9]), "+f"(d[10]), "+f"(d[11]), "+f"(d[12]), "+f"(d[13]), "+f"(d[14]), "+f"(d[15]), "+f"(d[16]), "+f"(d[17]), "+f"(d[18]), "+f"(d[19]), "+f"(d[20]), "+f"(d[21]), "+f"(d[22]), "+f"(d[23]), "+f"(d[24]), "+f"(d[25]), "+f"(d[26]), "+f"(d[27]), "+f"(d[28]), "+f"(d[29]), "+f"(d[30]), "+f"(d[31]), "+f"(d[32]), "+f"(d[33]), "+f"(d[34]), "+f"(d[35]), "+f"(d[36]), "+f"(d[37]), "+f"(d[38]), "+f"(d[39]), "+f"(d[40]), "+f"(d[41]), "+f"(d[42]), "+f"(d[43])
    : "r"(alo), "r"(blo), "n"(AOFF >> 4), "n"(BOFF >> 4), "r"(scale_d));
}
template <int AOFF, int BOFF>
__device__ __forceinline__ void wgmma_ss_n128(float (&d)[64], uint32_t alo, uint32_t blo, int scale_d) {
  asm volatile("{\n.reg .pred p;\n.reg .b32 al, bl;\n.reg .b64 ad, bd;\nsetp.ne.b32 p, %68, 0;\n"
    "add.u32 al, %64, %66;\nmov.b64 ad, {al, 0x40000040};\nadd.u32 bl, %65, %67;\nmov.b64 bd, {bl, 0x40000040};\n"
    "wgmma.mma_async.sync.aligned.m64n128k16.f32.bf16.bf16 {%0, %1, %2, %3, %4, %5, %6, %7, %8, %9, %10, %11, %12, %13, %14, %15, %16, %17, %18, %19, %20, %21, %22, %23, %24, %25, %26, %27, %28, %29, %30, %31, %32, %33, %34, %35, %36, %37, %38, %39, %40, %41, %42, %43, %44, %45, %46, %47, %48, %49, %50, %51, %52, %53, %54, %55, %56, %57, %58, %59, %60, %61, %62, %63}, ad, bd, p, 1, 1, 0, 1;\n}\n"
    : "+f"(d[0]), "+f"(d[1]), "+f"(d[2]), "+f"(d[3]), "+f"(d[4]), "+f"(d[5]), "+f"(d[6]), "+f"(d[7]), "+f"(d[8]), "+f"(d[9]), "+f"(d[10]), "+f"(d[11]), "+f"(d[12]), "+f"(d[13]), "+f"(d[14]), "+f"(d[15]), "+f"(d[16]), "+f"(d[17]), "+f"(d[18]), "+f"(d[19]), "+f"(d[20]), "+f"(d[21]), "+f"(d[22]), "+f"(d[23]), "+f"(d[24]), "+f"(d[25]), "+f"(d[26]), "+f"(d[27]), "+f"(d[28]), "+f"(d[29]), "+f"(d[30]), "+f"(d[31]), "+f"(d[32]), "+f"(d[33]), "+f"(d[34]), "+f"(d[35]), "+f"(d[36]), "+f"(d[37]), "+f"(d[38]), "+f"(d[39]), "+f"(d[40]), "+f"(d[41]), "+f"(d[42]), "+f"(d[43]), "+f"(d[44]), "+f"(d[45]), "+f"(d[46]), "+f"(d[47]), "+f"(d[48]), "+f"(d[49]), "+f"(d[50]), "+f"(d[51]), "+f"(d[52]), "+f"(d[53]), "+f"(d[54]), "+f"(d[55]), "+f"(d[56]), "+f"(d[57]), "+f"(d[58]), "+f"(d[59]), "+f"(d[60]), "+f"(d[61]), "+f"(d[62]), "+f"(d[63])
    : "r"(alo), "r"(blo), "n"(AOFF >> 4), "n"(BOFF >> 4), "r"(scale_d));
}

__device__ __forceinline__ uint32_t smem_u32(const void* p) { return (uint32_t)__cvta_generic_to_shared(p); }
__device__ __forceinline__ uint32_t mkdesc(uint32_t addr, uint32_t lbo) { return ((addr & 0x3FFFF) >> 4) | ((lbo >> 4) << 16); }
template <int I> struct IC { static constexpr int v = I; };
template <int B, int E, class F> __device__ __forceinline__ void static_for(F&& f) {
  if constexpr (B < E) { f(IC<B>{}); static_for<B + 1, E>(f); }
}
__device__ __forceinline__ void mbar_init(uint32_t bar, uint32_t cnt) { asm volatile("mbarrier.init.shared::cta.b64 [%0], %1;" :: "r"(bar), "r"(cnt)); }
__device__ __forceinline__ void mbar_expect_tx(uint32_t bar, uint32_t bytes) { asm volatile("mbarrier.arrive.expect_tx.shared::cta.b64 _, [%0], %1;" :: "r"(bar), "r"(bytes) : "memory"); }
__device__ __forceinline__ void mbar_arrive(uint32_t bar) { asm volatile("mbarrier.arrive.shared::cta.b64 _, [%0];" :: "r"(bar) : "memory"); }
__device__ __forceinline__ void mbar_arrive_remote(uint32_t raddr) { asm volatile("mbarrier.arrive.shared::cluster.b64 _, [%0];" :: "r"(raddr) : "memory"); }
__device__ __forceinline__ uint32_t mapa(uint32_t addr, uint32_t cta) { uint32_t r; asm("mapa.shared::cluster.u32 %0, %1, %2;" : "=r"(r) : "r"(addr), "r"(cta)); return r; }
__device__ __forceinline__ void mbar_wait(uint32_t bar, uint32_t parity) {
  asm volatile("{\n.reg .pred p;\n.reg .u32 n;\n"
    "mbarrier.try_wait.parity.shared::cta.b64 p, [%0], %1;\n@p bra W_DONE;\nmov.u32 n, 0;\n"
    "W_LOOP:\nmbarrier.try_wait.parity.shared::cta.b64 p, [%0], %1;\n@p bra W_DONE;\n"
    "add.u32 n, n, 1;\nsetp.lt.u32 p, n, 4194304;\n@p bra W_LOOP;\ntrap;\nW_DONE:\n}" :: "r"(bar), "r"(parity) : "memory");
}
__device__ __forceinline__ void tma_load(uint32_t dst, const CUtensorMap* tm, uint32_t bar, int c0, int c1) {
  asm volatile("cp.async.bulk.tensor.2d.shared::cluster.global.mbarrier::complete_tx::bytes [%0], [%1, {%3, %4}], [%2];"
    :: "r"(dst), "l"((uint64_t)tm), "r"(bar), "r"(c0), "r"(c1) : "memory");
}
__device__ __forceinline__ void bulk_load(uint32_t dst, const void* src, uint32_t bytes, uint32_t bar) {
  asm volatile("cp.async.bulk.shared::cluster.global.mbarrier::complete_tx::bytes [%0], [%1], %2, [%3];" :: "r"(dst), "l"(src), "r"(bytes), "r"(bar) : "memory");
}
__device__ __forceinline__ void bulk_store(void* dst, uint32_t src, uint32_t bytes) {
  asm volatile("cp.async.bulk.global.shared::cta.bulk_group [%0], [%1], %2;" :: "l"(dst), "r"(src), "r"(bytes) : "memory");
}
__device__ __forceinline__ void sts128(uint32_t addr, float a, float b, float c, float d) {
  asm volatile("st.shared.v4.f32 [%0], {%1,%2,%3,%4};" :: "r"(addr), "f"(a), "f"(b), "f"(c), "f"(d) : "memory");
}
__device__ __forceinline__ void wg_fence() { asm volatile("wgmma.fence.sync.aligned;" ::: "memory"); }
__device__ __forceinline__ void wg_commit() { asm volatile("wgmma.commit_group.sync.aligned;" ::: "memory"); }
template <int N> __device__ __forceinline__ void wg_wait() { asm volatile("wgmma.wait_group.sync.aligned %0;" :: "n"(N) : "memory"); }
template <int N> __device__ __forceinline__ void reg_fence(float (&d)[N]) {
#pragma unroll
  for (int i = 0; i < N; i++) asm volatile("" : "+f"(d[i]) :: "memory");
}
__device__ __forceinline__ uint32_t pack_bf16(float lo, float hi) { uint32_t r; asm("cvt.rn.bf16x2.f32 %0, %1, %2;" : "=r"(r) : "f"(hi), "f"(lo)); return r; }
__device__ __forceinline__ uint32_t pack_bf16v(float lo, float hi) { uint32_t r; asm volatile("cvt.rn.bf16x2.f32 %0, %1, %2;" : "=r"(r) : "f"(hi), "f"(lo)); return r; }
__device__ __forceinline__ float gelu2(float v) {
  float u = v * fmaf(v * v, 0.0356774081363f, 0.7978845608029f);
  float t; asm("tanh.approx.f32 %0, %1;" : "=f"(t) : "f"(u));
  return fmaf(v, t, v);
}
__device__ __forceinline__ void lds64v(float& a, float& b, uint32_t addr) { asm volatile("ld.volatile.shared.v2.f32 {%0, %1}, [%2];" : "=f"(a), "=f"(b) : "r"(addr)); }
__device__ __forceinline__ void lds64p(float& a, float& b, uint32_t base, uint32_t off) {
  asm volatile("{\n.reg .pred p;\nsetp.ne.u32 p, %2, 0;\n@p ld.volatile.shared.v2.f32 {%0, %1}, [%3];\n}" : "+f"(a), "+f"(b) : "r"(base), "r"(base + off));
}
__device__ __forceinline__ float4 lds128(uint32_t addr) { float4 v; asm volatile("ld.shared.v4.f32 {%0,%1,%2,%3}, [%4];" : "=f"(v.x), "=f"(v.y), "=f"(v.z), "=f"(v.w) : "r"(addr) : "memory"); return v; }
__device__ __forceinline__ unsigned ld_acquire(const unsigned* p) { unsigned v; asm volatile("ld.acquire.gpu.global.u32 %0, [%1];" : "=r"(v) : "l"(p) : "memory"); return v; }
__device__ __forceinline__ void flag_set(unsigned* p, unsigned v) { asm volatile("st.release.gpu.global.u32 [%0], %1;" :: "l"(p), "r"(v) : "memory"); }
__device__ __forceinline__ void flag_wait(const unsigned* p, unsigned tag) {
  uint32_t it = 0;
  while (ld_acquire(p) != tag) { __nanosleep(40); if (++it > (1u << 22)) __trap(); }
}
__device__ __forceinline__ uint32_t ldg32(const void* p) { uint32_t v; asm volatile("ld.global.u32 %0, [%1];" : "=r"(v) : "l"(p) : "memory"); return v; }
__device__ __forceinline__ void mma16816(float (&c)[4], uint32_t a0, uint32_t a1, uint32_t a2, uint32_t a3, uint32_t b0, uint32_t b1) {
  asm volatile("mma.sync.aligned.m16n8k16.row.col.f32.bf16.bf16.f32 {%0,%1,%2,%3}, {%4,%5,%6,%7}, {%8,%9}, {%0,%1,%2,%3};"
    : "+f"(c[0]), "+f"(c[1]), "+f"(c[2]), "+f"(c[3]) : "r"(a0), "r"(a1), "r"(a2), "r"(a3), "r"(b0), "r"(b1));
}
__device__ __forceinline__ void mma1688(float (&c)[4], uint32_t a0, uint32_t a1, uint32_t b0) {
  asm volatile("mma.sync.aligned.m16n8k8.row.col.f32.bf16.bf16.f32 {%0,%1,%2,%3}, {%4,%5}, {%6}, {%0,%1,%2,%3};"
    : "+f"(c[0]), "+f"(c[1]), "+f"(c[2]), "+f"(c[3]) : "r"(a0), "r"(a1), "r"(b0));
}
__device__ __forceinline__ uint32_t movmat(uint32_t a) { uint32_t d; asm volatile("movmatrix.sync.aligned.m8n8.trans.b16 %0, %1;" : "=r"(d) : "r"(a)); return d; }

__device__ __forceinline__ uint32_t fresh_tid() { uint32_t t; asm volatile("mov.u32 %0, %%tid.x;" : "=r"(t)); return t; }

__device__ __forceinline__ void add_partial(float (&acc)[32], uint32_t addr) {
#pragma unroll
  for (int h = 0; h < 2; h++) {
#pragma unroll
    for (int j = 4 * h; j < 4 * h + 4; j++) {
      const float4 v = lds128(addr + j * 2048);
      acc[4 * j] += v.x; acc[4 * j + 1] += v.y; acc[4 * j + 2] += v.z; acc[4 * j + 3] += v.w;
    }
    reg_fence(acc);
    __syncwarp();
  }
}

struct Params {
  const __nv_bfloat16 *x, *wqkv, *wo, *w1, *w2;
  const __nv_bfloat16* b1;
  const __nv_bfloat16* b2;
  const __nv_bfloat16* gate_w;
  __nv_bfloat16* out;
};

__device__ __forceinline__ int p2_block(int c, int t) {
  if (t == 0) return 8;
  int d = (t - 1) >> 1, second = (t - 1) & 1, r = c & 1;
  int j = ((c >> 1) - d) & 3;
  return 2 * j + (second ? r : 1 - r);
}

template <int U0, bool ZERO = false, class Epi>
__device__ __forceinline__ void ffn1_block128(float (&cur)[64], uint32_t bars, uint32_t xdesc, uint32_t bdesc, bool elect, Epi epi) {
  static_for<0, 9>([&](auto KB) {
    constexpr int kb = KB.v, u = U0 + kb, st = u % 5;
    mbar_wait(bars + (B_FULL + st) * 8, (u / 5) & 1);
    wg_fence();
    wgmma_ss_n128<kb * 16384, st * ST_BYTES>(cur, xdesc, bdesc, (ZERO && kb == 0) ? 0 : 1);
    wgmma_ss_n128<kb * 16384 + 32, st * ST_BYTES + 2048>(cur, xdesc, bdesc, 1);
    wg_commit();
    wg_wait<1>();
    if (elect) mbar_arrive(bars + (B_EMPTY + (u + 4) % 5) * 8);
    epi(2 * kb - 1);
    wg_fence();
    wgmma_ss_n128<kb * 16384 + 64, st * ST_BYTES + 4096>(cur, xdesc, bdesc, 1);
    wgmma_ss_n128<kb * 16384 + 96, st * ST_BYTES + 6144>(cur, xdesc, bdesc, 1);
    wg_commit();
    epi(2 * kb);
  });
}

template <int kb>
__device__ __forceinline__ void p2_kblock(float (&acc)[32], const uint32_t (&hf)[144], uint32_t bdesc, int init) {
  static_for<0, 4>([&](auto KS) {
    constexpr int k = kb * 4 + KS.v;
    wgmma_rs_n64<k * 2048>(acc, hf[4 * k], hf[4 * k + 1], hf[4 * k + 2], hf[4 * k + 3], bdesc, k > 0 ? 1 : init);
  });
}
__device__ __forceinline__ void p2_oblock(float (&acc)[32], const uint32_t (&of)[18], uint32_t bdesc, uint32_t odesc) {
  static_for<0, 4>([&](auto KS) {
    constexpr int ks = KS.v;
    wgmma_rs_n64<(36 + ks) * 2048>(acc, of[4 * ks], of[4 * ks + 1], of[4 * ks + 2], of[4 * ks + 3], bdesc, 1);
  });
  wgmma_rs_n64<0, 0x40000000>(acc, of[16], of[17], 0u, 0u, odesc, 1);
}

__global__ void __cluster_dims__(2, 1, 1) __launch_bounds__(384, 1)
fused_kernel(const __grid_constant__ CUtensorMap tm_x, const __grid_constant__ CUtensorMap tm_qkv,
             const __grid_constant__ CUtensorMap tm_w1, const __grid_constant__ CUtensorMap tm_w2,
             const __grid_constant__ CUtensorMap tm_wo, const __grid_constant__ CUtensorMap tm_wo8,
             const __grid_constant__ CUtensorMap tm_out, const __grid_constant__ CUtensorMap tm_xh, const Params prm) {
  extern __shared__ __align__(1024) uint8_t smem[];
  const uint32_t sb = smem_u32(smem);
  const uint32_t bars = sb + BAR_OFF;
  const int cta = blockIdx.x, m = cta >> 3, c = cta & 7;
  const int warp = __shfl_sync(~0u, threadIdx.x >> 5, 0), wg = warp >> 2, lane = threadIdx.x & 31;
  const int g = lane >> 2, q = lane & 3;

  uint32_t bw0[16];
  if (wg < 2) {
#pragma unroll
    for (int j = 0; j < 16; j++) bw0[j] = ldg32(prm.b1 + c * 576 + j * 8 + 2 * q);
  }
  if (lane == 0) {
    const int grp = warp == 8 ? 0 : warp == 0 ? 8 : warp;
    const uint32_t cnt = grp < 8 ? 1 : grp < 11 ? 2 : 4;
#pragma unroll
    for (int i = 0; i < 4; i++) mbar_init(bars + grp * 32 + i * 8, cnt);
    if (warp == 1) mbar_init(bars + B_BIAS * 8, 3);
    if (warp == 9) asm volatile("prefetch.tensormap [%0];" :: "l"((uint64_t)&tm_xh) : "memory");
    asm volatile("fence.mbarrier_init.release.cluster;" ::: "memory");
  }
  if (warp == 8) {
    asm volatile("bar.arrive 1, 384;" ::: "memory");
    if (lane == 0) {
      mbar_expect_tx(bars + B_XFULL0 * 8, 16384);
      tma_load(sb + X_OFF, &tm_x, bars + B_XFULL0 * 8, 0, m * 128);
      mbar_expect_tx(bars + B_FULL * 8, 16384);
      tma_load(sb + ST_OFF, &tm_qkv, bars + B_FULL * 8, c * 192, 0);
      tma_load(sb + ST_OFF + 8192, &tm_qkv, bars + B_FULL * 8, c * 192 + 64, 0);
      mbar_expect_tx(bars + (B_FULL + 1) * 8, 16384);
      tma_load(sb + ST_OFF + ST_BYTES, &tm_qkv, bars + (B_FULL + 1) * 8, c * 192 + 128, 0);
      tma_load(sb + ST_OFF + ST_BYTES + 8192, &tm_qkv, bars + (B_FULL + 1) * 8, 1536 + c * 24, 0);
    }
    asm volatile("bar.sync 6, 384;" ::: "memory");
  } else {
    asm volatile("bar.arrive 6, 384;" ::: "memory");
    asm volatile("bar.sync 1, 384;" ::: "memory");
  }
  asm volatile("barrier.cluster.arrive.relaxed.aligned;" ::: "memory");

  if (wg == 2) {
    asm volatile("setmaxnreg.dec.sync.aligned.u32 40;");
    if (warp == 8) {
      asm volatile("barrier.cluster.wait.acquire.aligned;" ::: "memory");
      if (lane == 0) {
        uint32_t st = 2, ph = 1;
        auto stage = [&](uint32_t bytes, const CUtensorMap* ta, int a0, int a1, const CUtensorMap* tb, int b0, int b1, bool two) {
          const uint32_t bar = bars + (B_FULL + st) * 8, dst = sb + ST_OFF + st * ST_BYTES;
          mbar_wait(bars + (B_EMPTY + st) * 8, ph);
          mbar_expect_tx(bar, bytes);
          tma_load(dst, ta, bar, a0, a1);
          if (two) tma_load(dst + 8192, tb, bar, b0, b1);
          if (++st == 5) { st = 0; ph ^= 1; }
        };
#pragma unroll 1
        for (int u = 2; u < 18; u++) {
          const int xk = u == 2 ? 1 : (u & 1) ? (u + 1) >> 1 : 9;
          if (xk < 9) {
            mbar_expect_tx(bars + (B_XFULL + xk) * 8, 16384);
            asm volatile("cp.async.bulk.tensor.2d.shared::cluster.global.mbarrier::complete_tx::bytes.multicast::cluster [%0], [%1, {%3, %4}], [%2], %5;"
              :: "r"(sb + X_OFF + xk * 16384 + (c & 1) * 8192), "l"((uint64_t)&tm_xh), "r"(bars + (B_XFULL + xk) * 8), "r"(xk * 64), "r"(m * 128 + (c & 1) * 64), "h"((uint16_t)3) : "memory");
          }
          const int c0 = c * 192 + (u & 1) * 128;
          stage(16384, &tm_qkv, c0, (u >> 1) * 64, &tm_qkv, (u & 1) ? 1536 + c * 24 : c0 + 64, (u >> 1) * 64, true);
          if (u == 12) {
            asm volatile("prefetch.tensormap [%0];" :: "l"((uint64_t)&tm_w1) : "memory");
            asm volatile("prefetch.tensormap [%0];" :: "l"((uint64_t)&tm_w2) : "memory");
            asm volatile("prefetch.tensormap [%0];" :: "l"((uint64_t)&tm_wo) : "memory");
            asm volatile("prefetch.tensormap [%0];" :: "l"((uint64_t)&tm_wo8) : "memory");
            asm volatile("prefetch.tensormap [%0];" :: "l"((uint64_t)&tm_out) : "memory");
          }
        }
#pragma unroll 1
        for (int b = 0; b < 4; b++)
#pragma unroll 1
          for (int kb = 0; kb < 9; kb++) stage(16384, &tm_w1, c * 576 + b * 128, kb * 64, &tm_w1, c * 576 + b * 128 + 64, kb * 64, true);
#pragma unroll 1
        for (int s = 0; s < 6; s++) {
          const bool two = s >= 1 && s <= 3;
          const int r0 = (s < 5 ? max(2 * s - 1, 0) : 8) * 64;
          stage(two ? 16384 : 8192, &tm_w1, c * 576 + 512, r0, &tm_w1, c * 576 + 512, r0 + 64, two);
        }
#pragma unroll 1
        for (int t = 0; t < 9; t++) {
          const int col = p2_block(c, t) * 64;
          const uint32_t set = (t & 1) * 5, base = sb + ((t & 1) ? ST2_OFF : ST_OFF);
          if (t == 1) mbar_wait(bars + B_XFREE * 8, 0);
#pragma unroll 1
          for (int s = 0; s < 5; s++) {
            const uint32_t bar = bars + (B_FULL + set + s) * 8, dst = base + s * ST_BYTES;
            mbar_wait(bars + (B_EMPTY + set + s) * 8, ((t >> 1) & 1) ^ 1);
            mbar_expect_tx(bar, s < 4 ? 16384 : 17408);
            tma_load(dst, &tm_w2, bar, col, c * 576 + s * 128);
            if (s < 4) {
              tma_load(dst + 8192, &tm_w2, bar, col, c * 576 + s * 128 + 64);
            } else {
              tma_load(dst + 8192, &tm_wo, bar, col, c * 72);
              tma_load(sb + WO8_OFF + (t & 1) * 1024, &tm_wo8, bar, col, c * 72 + 64);
            }
          }
        }
      }
    } else {
      const int wa = warp - 9;
      if (sb & 1023) __trap();
      const unsigned tag = (*(volatile unsigned*)&g_done >> 7) + 1;
      {
        uint32_t bw[3];
        uint4 gw[3];
#pragma unroll
        for (int i = 0; i < 3; i++) bw[i] = *(const uint32_t*)(prm.b1 + c * 576 + 2 * (wa * 32 + lane + 96 * i));
#pragma unroll
        for (int i = 0; i < 3; i++) gw[i] = *(const uint4*)(prm.gate_w + (wa + 3 * i) * 64 + (lane & 7) * 8);
#pragma unroll
        for (int i = 0; i < 3; i++)
          asm volatile("st.shared.v2.u32 [%0], {%1, %2};" :: "r"(sb + BIAS_OFF + (wa * 32 + lane + 96 * i) * 8), "r"(bw[i] << 16), "r"(bw[i] & 0xffff0000u) : "memory");
        __syncwarp();
        if (lane == 0) mbar_arrive(bars + B_BIAS * 8);
        float z[4] = {0.f, 0.f, 0.f, 0.f};
#pragma unroll
        for (int i = 0; i < 3; i++) {
          const uint32_t w4[4] = {gw[i].x, gw[i].y, gw[i].z, gw[i].w};
          mbar_wait(bars + (wa + i == 0 ? B_XFULL0 : B_XFULL + wa + 3 * i) * 8, 0);
#pragma unroll
          for (int rr = 0; rr < 4; rr++) {
            const int r = c * 16 + rr * 4 + (lane >> 3);
            const float4 xv = lds128(sb + X_OFF + (wa + 3 * i) * 16384 + r * 128 + (((lane ^ r) & 7) << 4));
            const uint32_t xa[4] = {__float_as_uint(xv.x), __float_as_uint(xv.y), __float_as_uint(xv.z), __float_as_uint(xv.w)};
#pragma unroll
            for (int e = 0; e < 4; e++)
              z[rr] = fmaf(__uint_as_float(xa[e] << 16), __uint_as_float(w4[e] << 16), fmaf(__uint_as_float(xa[e] & 0xffff0000u), __uint_as_float(w4[e] & 0xffff0000u), z[rr]));
          }
        }
#pragma unroll
        for (int rr = 0; rr < 4; rr++) {
#pragma unroll
          for (int o = 4; o; o >>= 1) z[rr] += __shfl_xor_sync(~0u, z[rr], o);
          if ((lane & 7) == 0) asm volatile("st.shared.f32 [%0], %1;" :: "r"(sb + ZP_OFF + (rr * 4 + (lane >> 3)) * 16 + wa * 4), "f"(z[rr]) : "memory");
        }
      }
      asm volatile("barrier.cluster.wait.acquire.aligned;" ::: "memory");
      asm volatile("bar.sync 2, 96;" ::: "memory");
      if (wa == 1 && lane < 16) {
        const float4 zp = lds128(sb + ZP_OFF + lane * 16);
        const float e = __expf(fminf(zp.x + zp.y + zp.z, 60.f));
        g_sg[m * 128 + c * 16 + lane] = make_float2(2.f * e, __fdividef(0.5f, 1.f + e));
      }
      __syncwarp();
      TSW(40 + wa);
      if (wa == 0) {
        if (lane == 0) {
          auto fetch = [&](int f) {
            const int src = m * 8 + ((c + (f == 2 ? 6 : 4)) & 7);
            flag_wait(&g_pflag[(src * 4 + f + 1) * FS], tag);
            asm volatile("fence.proxy.async.global;" ::: "memory");
            if (f == 1) mbar_wait(bars + (B_SFREE + 1) * 8, 0);
#pragma unroll 1
            for (int v = 0; v < 2; v++) {
              const uint32_t vb = bars + v * 8;
              if (f > 0) mbar_wait(vb + (B_EMPTY + 3 + 2 * f) * 8, 1); else mbar_wait(bars + B_SFREE * 8, 0);
              mbar_expect_tx(vb + (B_LFULL + 2 * f) * 8, 16384);
              bulk_load(sb + v * 16384 + (f == 0 ? SB_OFF : ST2_OFF + (f - 1) * 32768), g_part + (size_t)(src * 4 + f + 1) * 2048 + v * 1024, 16384, vb + (B_LFULL + 2 * f) * 8);
            }
          };
          mbar_wait(bars + B_SFREE * 8, 0);
          mbar_wait(bars + B_SFREE * 8, 1);
#pragma unroll 1
          for (int f = 0; f < 3; f++) {
            fetch(f);
          }
        }
      } else if (wa == 1) {
        if (lane == 0) {
          mbar_wait(bars + B_QDONE * 8, 0);
          mbar_wait(bars + (B_QDONE + 1) * 8, 0);
          TSW(44);
          flag_set(&g_qflag[cta * FS], tag);
          TSW(46);
#pragma unroll 1
          for (int e = 0; e < 4; e++) {
#pragma unroll 1
            for (int w = 0; w < 2; w++) {
              mbar_wait(bars + (B_PDONE + w) * 8, e & 1);
              bulk_store(g_part + (size_t)(cta * 4 + e) * 2048 + w * 1024, sb + w * 16384 + SB_OFF, 16384);
            }
            asm volatile("cp.async.bulk.commit_group;" ::: "memory");
            if (e == 3) mbar_arrive(bars + (B_SFREE + 1) * 8);
            asm volatile("cp.async.bulk.wait_group.read 0;" ::: "memory");
            mbar_arrive(bars + (e < 3 ? B_SFREE : B_SFREE + 2) * 8);
            asm volatile("cp.async.bulk.wait_group 0;" ::: "memory");
            asm volatile("fence.proxy.async.global;" ::: "memory");
            asm volatile("st.relaxed.gpu.global.u32 [%0], %1;" :: "l"(&g_pflag[(cta * 4 + e) * FS]), "r"(tag) : "memory");
          }
        }
      } else {
        mbar_wait(bars + (B_QDONE + 1) * 8, 0);
        if (lane < 8 || (lane < 16 && m > 0)) flag_wait(&g_qflag[(m * 8 + (lane < 8 ? lane : lane - 16)) * FS], tag);
        __syncwarp();
        if (lane == 0) mbar_arrive(bars + B_QREADY * 8);
        TSW(43);
        {
          const uint32_t bw = *(const uint32_t*)(prm.b2 + p2_block(c, 8) * 64 + 2 * lane);
          const uint32_t bw8 = *(const uint32_t*)(prm.b2 + 512 + 2 * lane);
          asm volatile("st.shared.v2.f32 [%0], {%1, %2};" :: "r"(sb + B2_OFF + lane * 8), "f"(2.f * __uint_as_float(bw << 16)), "f"(2.f * __uint_as_float(bw & 0xffff0000u)) : "memory");
          mbar_wait(bars + B_XFREE * 8, 0);
          asm volatile("st.shared.v2.f32 [%0], {%1, %2};" :: "r"(sb + B28_OFF + lane * 8), "f"(2.f * __uint_as_float(bw8 << 16)), "f"(2.f * __uint_as_float(bw8 & 0xffff0000u)) : "memory");
        }
        float sr[4];
#pragma unroll
        for (int i = 0; i < 4; i++) sr[i] = g_sg[m * 128 + lane * 4 + i].y;
        mbar_wait(bars + B_SFREE * 8, 0);
        if (lane < 8) flag_wait(&g_pflag[(m * 8 + lane) * 4 * FS], tag);
        __syncwarp();
        if (lane == 0) {
          asm volatile("fence.proxy.async.global;" ::: "memory");
          mbar_wait(bars + (B_SFREE + 2) * 8, 0);
          mbar_expect_tx(bars + (B_SFREE + 3) * 8, 32768);
#pragma unroll 1
          for (int i = 0; i < 8; i++) bulk_load(sb + SB_OFF + i * 4096, g_part + (size_t)(m * 8 + i) * 8192 + c * 256, 4096, bars + (B_SFREE + 3) * 8);
        }
        __syncwarp();
        mbar_wait(bars + (B_EMPTY + 9) * 8, 1);
        sts128(sb + SR_OFF + lane * 16, sr[0], sr[1], sr[2], sr[3]);
        __syncwarp();
        if (lane < 3) mbar_arrive(bars + B_BIAS * 8);
      }
      TSW(49 + wa);
    }
  } else {
    asm volatile("setmaxnreg.inc.sync.aligned.u32 232;");
    const bool elect = (threadIdx.x & 127) == 0;
    const uint32_t xdesc = mkdesc(sb + X_OFF + wg * 8192, 16);
    const uint32_t bdesc = mkdesc(sb + ST_OFF, 8192);
    const uint32_t bias_addr = sb + BIAS_OFF + q * 8;
    uint32_t hf[144], ow[2][9];
    float accB[64];
    {
      float accA[64];
#pragma unroll
      for (int j = 0; j < 16; j++) {
        const uint32_t bw = bw0[j];
        asm volatile("shl.b32 %0, %4, 16;\nand.b32 %1, %4, 0xffff0000;\nshl.b32 %2, %4, 16;\nand.b32 %3, %4, 0xffff0000;"
          : "=f"(accA[4 * j]), "=f"(accA[4 * j + 1]), "=f"(accA[4 * j + 2]), "=f"(accA[4 * j + 3]) : "r"(bw));
      }
      {
        float accQ[44];
        int st = 0; uint32_t ph = 0;
#pragma unroll 1
        for (int kb = 0; kb < 9; kb++) {
          const uint32_t ad = xdesc + kb * 1024;
          mbar_wait(bars + (kb == 0 ? B_XFULL0 : B_XFULL + kb) * 8, 0);
          mbar_wait(bars + (B_FULL + st) * 8, ph);
          if (kb == 0) TS(0);
          wg_fence();
          static_for<0, 4>([&](auto KS) { wgmma_ss_n128<KS.v * 32, KS.v * 2048>(accB, ad, bdesc + st * 1024, KS.v > 0 ? 1 : kb > 0); });
          wg_commit();
          if (kb > 0) {
            wg_wait<1>();
            if (elect) mbar_arrive(bars + (B_EMPTY + (st == 0 ? 4 : st - 1)) * 8);
          }
          if (++st == 5) { st = 0; ph ^= 1; }
          mbar_wait(bars + (B_FULL + st) * 8, ph);
          wg_fence();
          static_for<0, 4>([&](auto KS) { wgmma_ss_n88<KS.v * 32, KS.v * 2048>(accQ, ad, bdesc + st * 1024, KS.v > 0 ? 1 : kb > 0); });
          wg_commit();
          wg_wait<1>();
          if (elect) mbar_arrive(bars + (B_EMPTY + (st == 0 ? 4 : st - 1)) * 8);
          if (++st == 5) { st = 0; ph ^= 1; }
        }
        TS(1);
        char* qp = (char*)g_qkv + (size_t)(24 * c) * 32768 + (g & 1) * 16384 + (m * 8 + warp) * 128 + (g >> 1) * 32 + q * 8;
        char* qp2 = qp + (size_t)(168 - 21 * c) * 32768;
        ffn1_block128<18>(accA, bars, xdesc, bdesc, elect, [&](int i) {
          if (i < 0) { reg_fence(accQ); reg_fence(accB); mbar_wait(bars + B_BIAS * 8, 0); return; }
          if (i < QSL) {
#pragma unroll
            for (int j = (27 * i + QSL - 1) / QSL; j < (27 * i + 27 + QSL - 1) / QSL; j++) {
              if (j < 16) *(uint2*)(qp + j * 32768) = make_uint2(pack_bf16(accB[4 * j], accB[4 * j + 1]), pack_bf16(accB[4 * j + 2], accB[4 * j + 3]));
              else *(uint2*)((j < 24 ? qp : qp2) + j * 32768) = make_uint2(pack_bf16(accQ[4 * j - 64], accQ[4 * j - 63]), pack_bf16(accQ[4 * j - 62], accQ[4 * j - 61]));
            }
          }
          if (i == QSL) {
            __syncwarp();
            if (lane == 0) mbar_arrive(bars + (B_QDONE + wg) * 8);
          }
          if (i >= 6) {
#pragma unroll
            for (int p = 3 * (i - 6); p < 3 * (i - 5) && p < 32; p++) lds64p(accB[2 * p], accB[2 * p + 1], bias_addr, 512 + (p >> 1) * 32);
          }
        });
      }
      TS(2);
      uint32_t qa[2][9], kf[3][9], vf[3][9];
      float gs0, gs1;
      const int par = warp & 1, pr = m * 64 + (warp >> 1) * 16;
      const int row0 = (warp >> 1) * 32 + 2 * g + par;
      const char* abase = (const char*)g_qkv + (size_t)(9 * c) * 32768 + q * 8;
      const char* ap = abase + par * 16384 + (g & 3) * 32 + (g >> 2) * 4 + pr * 16;
      const char* ap0 = pr > 0 ? ap - 128 : abase;
      ffn1_block128<27>(accB, bars, xdesc, bdesc, elect, [&](int i) {
        if (i < 0) { reg_fence(accA); return; }
        if (i < 16) {
#pragma unroll
          for (int p = 2 * i; p < 2 * i + 2; p++) hf[p] = pack_bf16v(gelu2(accA[2 * p]), gelu2(accA[2 * p + 1]));
        }
        if (i >= ALS && i < ALS + 9) {
          const int j = i - ALS;
          if (j == 0) {
            mbar_wait(bars + B_QREADY * 8, 0);
            gs0 = g_sg[m * 128 + row0].x; gs1 = g_sg[m * 128 + row0 + 16].x;
          }
          qa[0][j] = ldg32(ap + j * 32768); qa[1][j] = ldg32(ap + j * 32768 + 128);
          kf[0][j] = ldg32(ap0 + (72 + j) * 32768); kf[1][j] = ldg32(ap + (72 + j) * 32768); kf[2][j] = ldg32(ap + (72 + j) * 32768 + 128);
          vf[0][j] = ldg32(ap0 + (144 + j) * 32768); vf[1][j] = ldg32(ap + (144 + j) * 32768); vf[2][j] = ldg32(ap + (144 + j) * 32768 + 128);
        }
      });
      TS(3);
      {
        const bool up0 = 2 * q > g, up1 = 2 * q + 1 > g;
        const uint32_t mk = (up0 ? 0xffffu : 0u) | (up1 ? 0xffff0000u : 0u);
        float l[4][4];
        static_for<0, 4>([&](auto H) {
          constexpr int h = H.v;
          const bool lo = q >= h, hi = q <= h;
          float s[3][4];
#pragma unroll
          for (int kt = 0; kt < 3; kt++) {
            s[kt][0] = s[kt][1] = s[kt][2] = s[kt][3] = 0.f;
            mma16816(s[kt], lo ? qa[0][2 * h] : 0u, lo ? qa[1][2 * h] : 0u, qa[0][2 * h + 1], qa[1][2 * h + 1], kf[kt][2 * h], kf[kt][2 * h + 1]);
            mma1688(s[kt], hi ? qa[0][2 * h + 2] : 0u, hi ? qa[1][2 * h + 2] : 0u, kf[kt][2 * h + 2]);
          }
          const float sc = 0.23570226039551584f * 1.4426950408889634f;
          l[h][0] = (up0 ? s[0][0] : s[1][0]) * sc; l[h][1] = (up1 ? s[0][1] : s[1][1]) * sc;
          l[h][2] = (up0 ? s[1][2] : s[2][2]) * sc; l[h][3] = (up1 ? s[1][3] : s[2][3]) * sc;
          if (pr == 0) { if (up0) l[h][0] = -1e9f * 1.4426950408889634f; if (up1) l[h][1] = -1e9f * 1.4426950408889634f; }
        });
        TS(30);
#pragma unroll
        for (int kt = 0; kt < 3; kt++)
#pragma unroll
          for (int j = 0; j < 9; j++) vf[kt][j] = movmat(vf[kt][j]);
        float mx[4][2], dn[4][2];
        uint32_t pt[4], pb[4];
#pragma unroll
        for (int h = 0; h < 4; h++) { mx[h][0] = fmaxf(l[h][0], l[h][1]); mx[h][1] = fmaxf(l[h][2], l[h][3]); }
#pragma unroll
        for (int o = 1; o <= 2; o++)
#pragma unroll
          for (int h = 0; h < 4; h++) { mx[h][0] = fmaxf(mx[h][0], __shfl_xor_sync(~0u, mx[h][0], o)); mx[h][1] = fmaxf(mx[h][1], __shfl_xor_sync(~0u, mx[h][1], o)); }
#pragma unroll
        for (int h = 0; h < 4; h++) {
#pragma unroll
          for (int e = 0; e < 4; e++) asm("ex2.approx.ftz.f32 %0, %1;" : "=f"(l[h][e]) : "f"(l[h][e] - mx[h][e >> 1]));
          dn[h][0] = l[h][0] + l[h][1]; dn[h][1] = l[h][2] + l[h][3];
        }
#pragma unroll
        for (int o = 1; o <= 2; o++)
#pragma unroll
          for (int h = 0; h < 4; h++) { dn[h][0] += __shfl_xor_sync(~0u, dn[h][0], o); dn[h][1] += __shfl_xor_sync(~0u, dn[h][1], o); }
#pragma unroll
        for (int h = 0; h < 4; h++) {
          const float f0 = __fdividef(gs0, dn[h][0]), f1 = __fdividef(gs1, dn[h][1]);
          pt[h] = pack_bf16(l[h][0] * f0, l[h][1] * f0); pb[h] = pack_bf16(l[h][2] * f1, l[h][3] * f1);
        }
#pragma unroll
        for (int i = 0; i < 12; i++) {
          const int h = i / 3, cgp = 2 * h + i % 3;
          float o[4] = {0.f, 0.f, 0.f, 0.f};
          mma16816(o, pt[h] & mk, 0u, pt[h] & ~mk, pb[h] & mk, vf[0][cgp], vf[1][cgp]);
          mma1688(o, 0u, pb[h] & ~mk, vf[2][cgp]);
          const uint32_t w0 = pack_bf16(o[0], o[1]), w1 = pack_bf16(o[2], o[3]);
          if (i % 3 == 0 && h > 0) { if (q >= h) { ow[0][cgp] = w0; ow[1][cgp] = w1; } }
          else { ow[0][cgp] = w0; ow[1][cgp] = w1; }
        }
        TS(31);
      }
    }
    float accC[32];
    {
      float accA[64];
      asm volatile("bar.sync 3, 256;" ::: "memory");
      TS(16);
      ffn1_block128<36, true>(accA, bars, xdesc, bdesc, elect, [&](int i) {
        if (i < 0) {
          reg_fence(accB);
          char* ob = (char*)g_o + (size_t)cta * 18432 + warp * 2304 + lane * 8;
#pragma unroll
          for (int j = 0; j < 9; j++) *(uint2*)(ob + j * 256) = make_uint2(ow[0][j], ow[1][j]);
          return;
        }
        if (i < 11) {
#pragma unroll
          for (int p = 3 * i; p < 3 * i + 3 && p < 32; p++) hf[32 + p] = pack_bf16v(gelu2(accB[2 * p]), gelu2(accB[2 * p + 1]));
        } else {
#pragma unroll
          for (int p = 6 * (i - 11); p < 6 * (i - 10) && p < 32; p++) lds64v(accB[2 * p], accB[2 * p + 1], bias_addr + 1536 + (p >> 1) * 32);
        }
      });
      TS(4);
      float bn[4];
      ffn1_block128<45>(accB, bars, xdesc, bdesc, elect, [&](int i) {
        if (i < 0) reg_fence(accA);
        if (i >= 0 && i < 12) {
#pragma unroll
          for (int k = (4 * i + 2) / 3; k < (4 * i + 6) / 3; k++) {
            const float bx = bn[2 * (k & 1)], by = bn[2 * (k & 1) + 1];
            hf[95 - 2 * k] = pack_bf16v(gelu2(accA[62 - 4 * k] + bx), gelu2(accA[63 - 4 * k] + by));
            hf[94 - 2 * k] = pack_bf16v(gelu2(accA[60 - 4 * k] + bx), gelu2(accA[61 - 4 * k] + by));
          }
        }
        if (i < 11) {
#pragma unroll
          for (int k = (4 * i + 6) / 3; k < (4 * i + 10) / 3; k++) lds64v(bn[2 * (k & 1)], bn[2 * (k & 1) + 1], bias_addr + 1024 + (15 - k) * 32);
        }
        if (i >= 12 && i < 16) {
#pragma unroll
          for (int p = 4 * (i - 12); p < 4 * (i - 11); p++) lds64v(accC[2 * p], accC[2 * p + 1], bias_addr + 2048 + (p >> 1) * 32);
        }
      });
    }
    TS(5);
    static_for<0, 18>([&](auto HB) {
      constexpr int hb = HB.v, kb = hb >> 1, s = kb < 7 ? (kb + 1) / 2 : kb - 3, u = 54 + s, st = u % 5;
      constexpr bool lead = kb == 0 || kb >= 7 || (kb & 1), first = lead && !(hb & 1);
      if (first) mbar_wait(bars + (B_FULL + st) * 8, (u / 5) & 1);
      wg_fence();
      static_for<(hb & 1) * 2, (hb & 1) * 2 + 2>([&](auto KS) {
        wgmma_ss_n64<kb * 16384 + KS.v * 32, st * ST_BYTES + (lead ? 0 : 8192) + KS.v * 2048>(accC, xdesc, bdesc, 1);
      });
      wg_commit();
      if (first) {
        wg_wait<1>();
        if (elect) mbar_arrive(bars + (B_EMPTY + (u + 4) % 5) * 8);
      }
      if (hb == 0) reg_fence(accB);
#pragma unroll
      for (int p = (B4P * hb + 17) / 18; p < (B4P * hb + B4P + 17) / 18; p++) {
        const int e = (p + 24) & 31;
        hf[96 + e] = pack_bf16v(gelu2(accB[2 * e]), gelu2(accB[2 * e + 1]));
      }
    });
    TS(6);
    asm volatile("bar.sync %0, 128;" :: "r"(7 + wg) : "memory");
    asm volatile("barrier.cluster.wait.acquire.aligned;" ::: "memory");
    const uint32_t peer = (c & 1) ^ 1;
    uint32_t of[18];
    float acc[32];
    {
      static_for<0, 18>([&](auto HB) {
        constexpr int hb = HB.v, s = hb >> 2;
        if (!(hb & 3)) mbar_wait(bars + (B_FULL + s) * 8, 0);
        wg_fence();
        static_for<2 * hb, 2 * hb + 2>([&](auto K) {
          constexpr int k = K.v;
          wgmma_rs_n64<k * 2048>(acc, hf[4 * k], hf[4 * k + 1], hf[4 * k + 2], hf[4 * k + 3], bdesc, k > 0);
        });
        if (hb == 17) p2_oblock(acc, of, bdesc, mkdesc(sb + WO8_OFF, 8192));
        wg_commit();
        if (!(hb & 3)) {
          wg_wait<1>();
          if (elect) mbar_arrive(bars + (B_EMPTY + (s + 4) % 5) * 8);
        }
        if (hb == 0) {
          reg_fence(accC);
          if (elect) { mbar_arrive(bars + B_XFREE * 8); mbar_arrive_remote(mapa(bars + B_PEERFREE * 8, peer)); }
        }
        if (hb < S0N) {
    #pragma unroll
          for (int p = B4P + ((48 - B4P) * hb + S0N - 1) / S0N; p < B4P + ((48 - B4P) * (hb + 1) + S0N - 1) / S0N; p++) {
            if (p < 32) hf[88 + p] = pack_bf16v(gelu2(accB[2 * ((p - 8) & 31)]), gelu2(accB[2 * ((p - 8) & 31) + 1]));
            else hf[96 + p] = pack_bf16v(gelu2(accC[2 * (p & 15)]), gelu2(accC[2 * (p & 15) + 1]));
          }
        }
        if (hb == S0L) {
          const uint32_t ft = fresh_tid();
          const char* op = (const char*)g_o + (size_t)cta * 18432 + ((warp & 6) + ((ft >> 2) & 1)) * 2304 + ((ft >> 3) & 3) * 32 + (ft & 3) * 8 + (warp & 1) * 4;
#pragma unroll
          for (int i = 0; i < 9; i++) { of[2 * i] = ldg32(op + i * 256); of[2 * i + 1] = ldg32(op + i * 256 + 128); }
        }
      });
      wg_wait<0>();
      reg_fence(acc);
      if (elect) mbar_arrive(bars + (B_EMPTY + 4) * 8);
    }
    const uint32_t rbase = sb + wg * 14336 + fresh_tid() * 16;
    mbar_wait(bars + B_XFREE * 8, 0);
#pragma unroll
    for (int j = 0; j < 8; j++) sts128(sb + SB_OFF + warp * 4096 + (rbase & 0x1f0) + j * 512, acc[4 * j], acc[4 * j + 1], acc[4 * j + 2], acc[4 * j + 3]);
    asm volatile("fence.proxy.async.shared::cta;" ::: "memory");
    __syncwarp();
    if (lane == 0) mbar_arrive(bars + (B_PDONE + wg) * 8);
    TS(7);
    const uint32_t wbars = __shfl_sync(~0u, bars + wg * 8, 0);
#pragma unroll 1
    for (int t = 1; t < 9; t++) {
      const uint32_t ph = (t >> 1) & 1, sbars = bars + (t & 1) * 40;
      const uint32_t sdesc = mkdesc(sb + ((t & 1) ? ST2_OFF : ST_OFF), 8192), odesc = mkdesc(sb + WO8_OFF + (t & 1) * 1024, 8192);
      if (wg == 1) asm volatile("bar.sync %0, 256;" :: "r"(4 + (t & 1)) : "memory");
      static_for<0, 5>([&](auto S) {
        constexpr int s = S.v;
        PACC_B();
        mbar_wait(sbars + (B_FULL + s) * 8, ph);
        PACC_E(0);
        wg_fence();
        p2_kblock<2 * s>(acc, hf, sdesc, 0);
        if constexpr (s < 4) p2_kblock<2 * s + 1>(acc, hf, sdesc, 1); else p2_oblock(acc, of, sdesc, odesc);
        wg_commit();
        if (s == STAGGER && wg == 0) asm volatile("bar.arrive %0, 256;" :: "r"(4 + (t & 1)) : "memory");
        if (s > 0) {
          wg_wait<1>();
          if (elect) mbar_arrive(sbars + (B_EMPTY + s - 1) * 8);
        }
      });
      wg_wait<0>();
      reg_fence(acc);
      PACC_B();
      if (elect) mbar_arrive(sbars + (B_EMPTY + 4) * 8);
      if (t & 1) {
        if (t == 1) mbar_wait(bars + B_PEERFREE * 8, 0);
        mbar_wait(wbars + B_QDONE * 8, ph);
        const uint32_t rdst = mapa(rbase + DS_OFF, peer), rbar = mapa(wbars + B_DFULL * 8, peer);
#pragma unroll
        for (int j = 0; j < 8; j++)
          asm volatile("st.async.weak.shared::cluster.mbarrier::complete_tx::bytes.v4.f32 [%0], {%1,%2,%3,%4}, [%5];"
            :: "r"(rdst + j * 2048), "f"(acc[4 * j]), "f"(acc[4 * j + 1]), "f"(acc[4 * j + 2]), "f"(acc[4 * j + 3]), "r"(rbar) : "memory");
        if (elect) mbar_expect_tx(wbars + B_DFULL * 8, 16384);
      } else {
        mbar_wait(wbars + B_DFULL * 8, ph ^ 1);
        add_partial(acc, rbase + DS_OFF);
        if (t < 8) {
          if (lane == 0) mbar_arrive_remote(mapa(wbars + B_QDONE * 8, peer));
          if (t == 6) {
            mbar_wait(wbars + B_LFULL * 8, 0);
            add_partial(acc, rbase + SB_OFF);
          } else {
            mbar_wait(bars + B_SFREE * 8, ph ^ 1);
          }
#pragma unroll
          for (int j = 0; j < 8; j++) sts128(rbase + SB_OFF + j * 2048, acc[4 * j], acc[4 * j + 1], acc[4 * j + 2], acc[4 * j + 3]);
          asm volatile("fence.proxy.async.shared::cta;" ::: "memory");
          __syncwarp();
          if (lane == 0) mbar_arrive(wbars + B_PDONE * 8);
        }
      }
      PACC_E(1);
      TS(7 + t);
    }
    {
      const uint32_t ft = fresh_tid();
      const uint32_t ost = sb + ST2_OFF + 65536 + (ft >> 5) * 2048 + ((ft >> 2) & 7) * 128 + (ft & 3) * 4;
      mbar_wait(bars + B_BIAS * 8, 1);
      float s0, s1;
      asm volatile("ld.shared.f32 %0, [%1];" : "=f"(s0) : "r"(sb + SR_OFF + (ft >> 5) * 64 + (ft & 28)) : "memory");
      asm volatile("ld.shared.f32 %0, [%1];" : "=f"(s1) : "r"(sb + SR_OFF + (ft >> 5) * 64 + 32 + (ft & 28)) : "memory");
      mbar_wait(wbars + (B_LFULL + 2) * 8, 0);
      mbar_wait(wbars + (B_LFULL + 4) * 8, 0);
#pragma unroll
      for (int j = 0; j < 8; j++) {
        float4 v = lds128(rbase + ST2_OFF + 32768 + j * 2048);
        const float4 w = lds128(rbase + ST2_OFF + j * 2048);
        v.x += w.x; v.y += w.y; v.z += w.z; v.w += w.w;
        float bx, by;
        lds64v(bx, by, sb + B2_OFF + (ft & 3) * 8 + j * 32);
        const uint32_t a = ost + ((j ^ ((ft >> 2) & 7)) << 4);
        asm volatile("st.shared.u32 [%0], %1;" :: "r"(a), "r"(pack_bf16((acc[4 * j] + v.x + bx) * s0, (acc[4 * j + 1] + v.y + by) * s0)) : "memory");
        asm volatile("st.shared.u32 [%0], %1;" :: "r"(a + 1024), "r"(pack_bf16((acc[4 * j + 2] + v.z + bx) * s1, (acc[4 * j + 3] + v.w + by) * s1)) : "memory");
      }
      asm volatile("fence.proxy.async.shared::cta;" ::: "memory");
      __syncwarp();
      if (lane == 0) {
        asm volatile("cp.async.bulk.tensor.2d.global.shared::cta.bulk_group [%0, {%2, %3}], [%1];"
          :: "l"((uint64_t)&tm_out), "r"(sb + ST2_OFF + 65536 + warp * 2048), "r"(p2_block(c, 8) * 64), "r"(m * 128 + warp * 16) : "memory");
        asm volatile("cp.async.bulk.commit_group;" ::: "memory");
      }
      mbar_wait(bars + (B_SFREE + 3) * 8, 0);
      {
        float4 a = lds128(sb + SB_OFF + ft * 16);
#pragma unroll
        for (int i = 1; i < 8; i++) { const float4 v = lds128(sb + SB_OFF + i * 4096 + ft * 16); a.x += v.x; a.y += v.y; a.z += v.z; a.w += v.w; }
        float bx, by, t0, t1;
        lds64v(bx, by, sb + B28_OFF + (ft >> 5) * 32 + (ft & 3) * 8);
        asm volatile("ld.shared.f32 %0, [%1];" : "=f"(t0) : "r"(sb + SR_OFF + c * 64 + (ft & 28)));
        asm volatile("ld.shared.f32 %0, [%1];" : "=f"(t1) : "r"(sb + SR_OFF + c * 64 + 32 + (ft & 28)));
        __nv_bfloat16* o8 = prm.out + (size_t)(m * 128 + c * 16 + ((ft >> 2) & 7)) * DM + 512 + (ft >> 5) * 8 + 2 * (ft & 3);
        *(uint32_t*)o8 = pack_bf16((a.x + bx) * t0, (a.y + by) * t0);
        *(uint32_t*)(o8 + 8 * DM) = pack_bf16((a.z + bx) * t1, (a.w + by) * t1);
      }
      if (lane == 0) asm volatile("cp.async.bulk.wait_group.read 0;" ::: "memory");
    }
    TS(17);
    if (threadIdx.x == 0) atomicAdd(&g_done, 1u);
  }
}

typedef CUresult (*EncodeFn)(CUtensorMap*, CUtensorMapDataType, cuuint32_t, void*, const cuuint64_t*, const cuuint64_t*,
                             const cuuint32_t*, const cuuint32_t*, CUtensorMapInterleave, CUtensorMapSwizzle,
                             CUtensorMapL2promotion, CUtensorMapFloatOOBfill);

CUtensorMap make_map(EncodeFn enc, const void* ptr, uint64_t rows, uint64_t cols, uint32_t box_rows) {
  CUtensorMap tm;
  cuuint64_t gd[2] = {cols, rows}; cuuint64_t gs[1] = {cols * 2};
  cuuint32_t bd[2] = {64, box_rows}; cuuint32_t es[2] = {1, 1};
  enc(&tm, CU_TENSOR_MAP_DATA_TYPE_BFLOAT16, 2, const_cast<void*>(ptr), gd, gs, bd, es, CU_TENSOR_MAP_INTERLEAVE_NONE,
      CU_TENSOR_MAP_SWIZZLE_128B, CU_TENSOR_MAP_L2_PROMOTION_L2_128B, CU_TENSOR_MAP_FLOAT_OOB_FILL_NONE);
  return tm;
}

}

extern "C" void kernel_launch(void* const* d_in, const int* in_sizes, int n_in, void* d_out, int out_size) {
  static EncodeFn enc = nullptr;
  if (!enc) {
    void* fn = nullptr; cudaDriverEntryPointQueryResult qr;
    cudaGetDriverEntryPoint("cuTensorMapEncodeTiled", &fn, cudaEnableDefault, &qr);
    enc = (EncodeFn)fn;
    cudaFuncSetAttribute(fused_kernel, cudaFuncAttributeMaxDynamicSharedMemorySize, SMEM_TOTAL);
  }
  CUtensorMap tx = make_map(enc, d_in[0], SEQ, DM, 128);
  CUtensorMap tq = make_map(enc, d_in[1], DM, 3 * DM, 64);
  CUtensorMap to = make_map(enc, d_in[2], DM, DM, 64);
  CUtensorMap to8 = make_map(enc, d_in[2], DM, DM, 8);
  CUtensorMap t1 = make_map(enc, d_in[4], DM, FF, 64);
  CUtensorMap t2 = make_map(enc, d_in[6], FF, DM, 64);
  CUtensorMap tout = make_map(enc, d_out, SEQ, DM, 16);
  CUtensorMap txh = make_map(enc, d_in[0], SEQ, DM, 64);
  Params prm;
  prm.x = (const __nv_bfloat16*)d_in[0];
  prm.wqkv = (const __nv_bfloat16*)d_in[1];
  prm.wo = (const __nv_bfloat16*)d_in[2];
  prm.w1 = (const __nv_bfloat16*)d_in[4];
  prm.w2 = (const __nv_bfloat16*)d_in[6];
  prm.b1 = (const __nv_bfloat16*)d_in[5];
  prm.b2 = (const __nv_bfloat16*)d_in[7];
  prm.gate_w = (const __nv_bfloat16*)d_in[8];
  prm.out = (__nv_bfloat16*)d_out;
  fused_kernel<<<NCTA, 384, SMEM_TOTAL, cudaStreamPerThread>>>(tx, tq, t1, t2, to, to8, tout, txh, prm);
}
```
